```python
import torch

def _softmax(x, axis=-1):
    return torch.softmax(x, dim=axis)

def _gelu(x):
    return torch.nn.functional.gelu(x, approximate='tanh')

def _silu(x):
    return torch.nn.functional.silu(x)

def _sigmoid(x):
    return torch.sigmoid(x)

def _layernorm(x, axis=-1, eps=1e-05):
    m = x.mean(dim=axis, keepdim=True)
    v = x.var(dim=axis, keepdim=True, unbiased=False)
    return (x - m) / torch.sqrt(v + eps)

def _scatter_add(tgt, idx, src, axis=0):
    return tgt.clone().index_add_(axis, idx, src)

def _segment_sum(src, seg, n):
    out = torch.zeros((n,) + src.shape[1:], dtype=src.dtype)
    return out.index_add_(0, seg, src)

def _pad(x, pw):
    flat = tuple((v for pair in reversed(pw) for v in pair))
    return torch.nn.functional.pad(x, flat)
kernel_name = 'adaLN_cond__gqa_block_cached__glu_gated_bilinear__decode'

def setup_inputs():

    _w = lambda a: (lambda t: t.to(torch.bfloat16) if t.is_floating_point() else t)(torch.as_tensor(a))

    def _A_setup():
        B, Sq, D = (1, 1, 576)
        Hq, Hkv, Sk, Dh = (32, 16, 65536, 128)
        assert Hq % Hkv == 0, (Hq, Hkv)
        return {'x': _w((lambda *s: torch.randn(*s, dtype=torch.bfloat16) * 0.05)(B, Sq, D)), 'k_cache': _w((lambda *s: torch.randn(*s, dtype=torch.bfloat16) * 0.8)(B, Hkv, Sk, Dh)), 'v_cache': _w((lambda *s: torch.randn(*s, dtype=torch.bfloat16) * 3.2)(B, Hkv, Sk, Dh)), 'wq': _w((lambda *s: torch.randn(*s, dtype=torch.bfloat16) * 0.8)(D, Hq * Dh) * D ** (-0.5)), 'wo': _w((lambda *s: torch.randn(*s, dtype=torch.bfloat16) * 3.2)(Hq * Dh, D) * (Hq * Dh) ** (-0.5))}
    _A_in = _A_setup()

    def _B_setup():
        B, S, D, F = (1, 1, 576, 4608)
        return {'x': _w((lambda *s: torch.randn(*s, dtype=torch.bfloat16) * 0.05)(B, S, D)), 'w_gate': _w((lambda *s: torch.randn(*s, dtype=torch.bfloat16) * 3.2)(D, F) * D ** (-0.5)), 'w_up': _w((lambda *s: torch.randn(*s, dtype=torch.bfloat16) * 3.2)(D, F) * D ** (-0.5)), 'w_down': _w((lambda *s: torch.randn(*s, dtype=torch.bfloat16) * 3.2)(F, D) * F ** (-0.5))}
    _B_in = _B_setup()
    return {'A_x': _A_in['x'], 'A_k_cache': _A_in['k_cache'], 'A_v_cache': _A_in['v_cache'], 'A_wq': _A_in['wq'], 'A_wo': _A_in['wo'], 'B_x': _B_in['x'], 'B_w_gate': _B_in['w_gate'], 'B_w_up': _B_in['w_up'], 'B_w_down': _B_in['w_down'], 'c': _w((lambda *s: torch.randn(*s, dtype=torch.bfloat16) * 0.2)(1, 576) * 8.0), 'w_mod': _w((lambda *s: torch.randn(*s, dtype=torch.bfloat16) * 0.2)(576, 6 * 576) * 576 ** (-0.5) * 8.0)}

def reference(A_x, A_k_cache, A_v_cache, A_wq, A_wo, B_x, B_w_gate, B_w_up, B_w_down, c, w_mod):

    def _A_ref(x, k_cache, v_cache, wq, wo):
        B, Sq, D = x.shape
        Hq, Dh = (32, 128)
        Hkv = k_cache.shape[1]
        rep = Hq // Hkv
        q = (lambda x, *d: x.permute(*d))((x @ wq).reshape(B, Sq, Hq, Dh), 0, 2, 1, 3)
        k = (lambda x, n, axis: torch.repeat_interleave(x, n, dim=axis))(k_cache, rep, axis=1)
        v = (lambda x, n, axis: torch.repeat_interleave(x, n, dim=axis))(v_cache, rep, axis=1)
        scores = torch.einsum('bhqd,bhkd->bhqk', q, k) * Dh ** (-0.5)
        p = _softmax(scores, axis=-1)
        o = torch.einsum('bhqk,bhkd->bhqd', p, v)
        return (lambda x, *d: x.permute(*d))(o, 0, 2, 1, 3).reshape(B, Sq, Hq * Dh) @ wo

    def _B_ref(x, w_gate, w_up, w_down):
        g = torch.einsum('bsd,df->bsf', x, w_gate)
        u = torch.einsum('bsd,df->bsf', x, w_up)
        h = g * u
        return torch.einsum('bsf,fd->bsd', h, w_down)
    x = A_x
    mod = (_silu(c) @ w_mod).reshape(c.shape[0], 6, 1, -1)
    sa, ca, ga, sb, cb, gb = (mod[:, 0].clone(), mod[:, 1].clone(), mod[:, 2].clone(), mod[:, 3].clone(), mod[:, 4].clone(), mod[:, 5].clone())
    h = _layernorm(x, axis=-1) * (1 + ca) + sa
    x = x + ga * _A_ref(h, A_k_cache, A_v_cache, A_wq, A_wo)
    h = _layernorm(x, axis=-1) * (1 + cb) + sb
    x = x + gb * _B_ref(h, B_w_gate, B_w_up, B_w_down)
    return x
```

```cpp
#include <cuda_runtime.h>
#include <cuda_bf16.h>
#include <cuda.h>
#include <stdint.h>

namespace {

constexpr int DM = 576;
constexpr int SK = 65536;
constexpr int HKV = 16;
constexpr int FF = 4608;
constexpr int NCTA = 132;
constexpr int NW = 128;
constexpr int MOD_C0 = 24;
constexpr int NRED = 72;

constexpr int TILE = 32;
constexpr int TPH = SK / TILE;
constexpr int NSTATIC = (HKV - 1) * TPH;
constexpr int NPOOL = TPH;
constexpr int ITEM = TILE * 256;

#define D_MAIN 6
#define D_POOL 5
#define D_TAIL 4
constexpr int D_PRO = 5;
constexpr int DMAX = 8;

constexpr int NCW = 9;
constexpr int NAS = 8;
constexpr int NAP = 5;
constexpr int W_PROD = 9, W_RED = 10;
constexpr int NTHREADS = 11 * 32;

constexpr int OFF_WMOD = 0;
constexpr int OFF_WQ = 9 * 4096;
constexpr int OFF_WO = 0;
constexpr int OFF_GATE = 9 * 4096;
constexpr int OFF_UP = OFF_GATE + 9 * 5120;
constexpr int OFF_RING = OFF_UP + 9 * 5120;
constexpr int OFF_SLOT0 = OFF_RING - 2 * (NAS - NAP) * ITEM;
constexpr int OFF_DOWN = OFF_RING;
constexpr int OFF_BAR = OFF_RING + 2 * NAP * ITEM;
constexpr int OFF_STAGE = OFF_BAR + 512;
constexpr int OFF_RED = OFF_STAGE + NAS * 260 * 4;
constexpr int OFF_Q = OFF_RED + 2 * 9 * 80 * 4;
constexpr int OFF_STAT = OFF_Q + 3 * 256 * 2;
constexpr int OFF_NTOT = OFF_STAT + 2 * 20 * 4;
constexpr int SMEM_BYTES = OFF_NTOT + 16;
static_assert(SMEM_BYTES <= 232448, "smem");
static_assert(OFF_SLOT0 >= OFF_WQ + 9 * 4096 && OFF_SLOT0 % 1024 == 0, "slots");

constexpr int B_FULL = 0, B_EMPTY = 2 * NAS, B_WO = 4 * NAS, B_GU = B_WO + 5, B_DOWN = B_GU + 9, B_PRO = B_DOWN + 5,
              B_END = B_PRO + 5;
static_assert(B_END <= 64, "barriers");

constexpr float NEG_BIG = -1.0e30f;
constexpr uint32_t SPIN_LIMIT = 1u << 22;

struct Maps { CUtensorMap k, v, wo, gate, up, down; };

__device__ uint32_t g_epoch;
__device__ uint32_t g_ticket;
__device__ __align__(128) uint32_t g_mod[6 * DM];
__device__ __align__(128) uint32_t g_q[4096];
__device__ __align__(128) uint32_t g_part[NCTA * 3 * 2 * 128];
__device__ __align__(128) uint32_t g_ml[NCTA * 3 * 2 * 4];
__device__ __align__(128) uint32_t g_y[NRED * NW * 8];
__device__ __align__(128) uint32_t g_x1[DM];
__device__ __align__(128) uint32_t g_z[NRED * NW * 8];

#define TL(i)
#define TL0(i)

__device__ __forceinline__ void mbar_init(uint32_t b, uint32_t c) {
    asm volatile("mbarrier.init.shared::cta.b64 [%0], %1;" ::"r"(b), "r"(c) : "memory");
}
__device__ __forceinline__ void mbar_expect(uint32_t b, uint32_t bytes) {
    asm volatile("mbarrier.arrive.expect_tx.shared::cta.b64 _, [%0], %1;" ::"r"(b), "r"(bytes) : "memory");
}
__device__ __forceinline__ void mbar_arrive(uint32_t b) {
    asm volatile("mbarrier.arrive.shared::cta.b64 _, [%0];" ::"r"(b) : "memory");
}
__device__ __forceinline__ bool mbar_try(uint32_t b, uint32_t ph) {
    uint32_t ok;
    asm volatile("{\n.reg .pred p;\nmbarrier.try_wait.parity.shared::cta.b64 p, [%1], %2;\nselp.u32 %0, 1, 0, p;\n}"
                 : "=r"(ok) : "r"(b), "r"(ph) : "memory");
    return ok;
}
__device__ __forceinline__ bool mbar_test(uint32_t b, uint32_t ph) {
    uint32_t ok;
    asm volatile("{\n.reg .pred p;\nmbarrier.test_wait.parity.shared::cta.b64 p, [%1], %2;\nselp.u32 %0, 1, 0, p;\n}"
                 : "=r"(ok) : "r"(b), "r"(ph) : "memory");
    return ok;
}
__device__ __forceinline__ void mbar_wait(uint32_t b, uint32_t ph) {
    uint32_t n = 0;
    while (!mbar_try(b, ph)) { if (++n > SPIN_LIMIT) __trap(); }
}
__device__ __forceinline__ void tma2d(uint32_t dst, const CUtensorMap* m, int c0, int c1, uint32_t bar, uint64_t pol) {
    asm volatile("cp.async.bulk.tensor.2d.shared::cluster.global.mbarrier::complete_tx::bytes.L2::cache_hint "
                 "[%0], [%1, {%3, %4}], [%2], %5;"
                 ::"r"(dst), "l"(m), "r"(bar), "r"(c0), "r"(c1), "l"(pol) : "memory");
}
__device__ __forceinline__ void bar_sync(int id, int n) { asm volatile("bar.sync %0, %1;" ::"r"(id), "r"(n) : "memory"); }
__device__ __forceinline__ void ldsm4(uint32_t a, uint32_t (&r)[4]) {
    asm volatile("ldmatrix.sync.aligned.m8n8.x4.shared.b16 {%0,%1,%2,%3}, [%4];"
                 : "=r"(r[0]), "=r"(r[1]), "=r"(r[2]), "=r"(r[3]) : "r"(a) : "memory");
}
__device__ __forceinline__ void ldsm4t(uint32_t a, uint32_t (&r)[4]) {
    asm volatile("ldmatrix.sync.aligned.m8n8.x4.trans.shared.b16 {%0,%1,%2,%3}, [%4];"
                 : "=r"(r[0]), "=r"(r[1]), "=r"(r[2]), "=r"(r[3]) : "r"(a) : "memory");
}
__device__ __forceinline__ void mma16816(float (&c)[4], const uint32_t (&a)[4], uint32_t b0, uint32_t b1) {
    asm volatile("mma.sync.aligned.m16n8k16.row.col.f32.bf16.bf16.f32 {%0,%1,%2,%3}, {%4,%5,%6,%7}, {%8,%9}, {%0,%1,%2,%3};"
                 : "+f"(c[0]), "+f"(c[1]), "+f"(c[2]), "+f"(c[3])
                 : "r"(a[0]), "r"(a[1]), "r"(a[2]), "r"(a[3]), "r"(b0), "r"(b1));
}
__device__ __forceinline__ uint32_t movmat(uint32_t a) {
    uint32_t d; asm volatile("movmatrix.sync.aligned.m8n8.trans.b16 %0, %1;" : "=r"(d) : "r"(a)); return d;
}
__device__ __forceinline__ float ex2(float x) { float y; asm("ex2.approx.ftz.f32 %0, %1;" : "=f"(y) : "f"(x)); return y; }
__device__ __forceinline__ uint32_t pack2(float lo, float hi) {
    uint32_t r; asm("cvt.rn.bf16x2.f32 %0, %1, %2;" : "=r"(r) : "f"(hi), "f"(lo)); return r;
}
__device__ __forceinline__ float rbf(float x) { return __uint_as_float(pack2(0.f, x)); }
__device__ __forceinline__ float rcp(float x) { float y; asm("rcp.approx.ftz.f32 %0, %1;" : "=f"(y) : "f"(x)); return y; }
__device__ __forceinline__ float blo(uint32_t p) { return __uint_as_float(p << 16); }
__device__ __forceinline__ float bhi(uint32_t p) { return __uint_as_float(p & 0xffff0000u); }

__device__ __forceinline__ uint32_t tagw(float v, uint32_t tag) { return (__float_as_uint(v) & ~3u) | tag; }
__device__ __forceinline__ float untag(uint32_t w) { return __uint_as_float(w & ~3u); }
__device__ __forceinline__ void stg1(uint32_t* p, uint32_t a) {
    asm volatile("st.relaxed.gpu.global.u32 [%0], %1;" ::"l"(p), "r"(a) : "memory");
}
__device__ __forceinline__ void stg2(uint32_t* p, uint32_t a, uint32_t b) {
    asm volatile("st.relaxed.gpu.global.v2.u32 [%0], {%1,%2};" ::"l"(p), "r"(a), "r"(b) : "memory");
}
__device__ __forceinline__ void stg4(uint32_t* p, uint32_t a, uint32_t b, uint32_t c, uint32_t d) {
    asm volatile("st.relaxed.gpu.global.v4.u32 [%0], {%1,%2,%3,%4};" ::"l"(p), "r"(a), "r"(b), "r"(c), "r"(d) : "memory");
}
__device__ __forceinline__ uint2 ldg2(const uint32_t* p) {
    uint2 v; asm volatile("ld.relaxed.gpu.global.v2.u32 {%0,%1}, [%2];" : "=r"(v.x), "=r"(v.y) : "l"(p) : "memory"); return v;
}
__device__ __forceinline__ uint4 ldg4(const uint32_t* p) {
    uint4 v;
    asm volatile("ld.relaxed.gpu.global.v4.u32 {%0,%1,%2,%3}, [%4];" : "=r"(v.x), "=r"(v.y), "=r"(v.z), "=r"(v.w) : "l"(p) : "memory");
    return v;
}
__device__ __forceinline__ uint32_t bad2(uint2 v, uint32_t tag) { return ((v.x ^ tag) | (v.y ^ tag)) & 3u; }
__device__ __forceinline__ uint32_t bad4(uint4 v, uint32_t tag) {
    return ((v.x ^ tag) | (v.y ^ tag) | (v.z ^ tag) | (v.w ^ tag)) & 3u;
}
__device__ __forceinline__ void spin_guard(uint32_t& n) { if (++n > SPIN_LIMIT) __trap(); }

__device__ __forceinline__ void ln_stats_part(float a, float b, float* stat, int warp, int lane) {
    float s = a + b, q = a * a + b * b;
#pragma unroll
    for (int o = 16; o; o >>= 1) { s += __shfl_xor_sync(0xffffffffu, s, o); q += __shfl_xor_sync(0xffffffffu, q, o); }
    if (lane == 0) *reinterpret_cast<float2*>(stat + 2 * warp) = make_float2(s, q);
}
__device__ __forceinline__ void ln_stats_fin(const float* stat, float& mean, float& rsd) {
    const float4 a = *reinterpret_cast<const float4*>(stat), b = *reinterpret_cast<const float4*>(stat + 4),
                 c = *reinterpret_cast<const float4*>(stat + 8), d = *reinterpret_cast<const float4*>(stat + 12);
    const float2 e = *reinterpret_cast<const float2*>(stat + 16);
    const float mu = (((a.x + a.z) + (b.x + b.z)) + ((c.x + c.z) + (d.x + d.z)) + e.x) * (1.0f / DM);
    const float sq = (((a.y + a.w) + (b.y + b.w)) + ((c.y + c.w) + (d.y + d.w)) + e.y) * (1.0f / DM);
    mean = rbf(mu);
    const float v = rbf(rbf(fmaxf(fmaf(-mu, mu, sq), 0.f)) + 1e-5f);
    float sd;
    asm("sqrt.approx.ftz.f32 %0, %1;" : "=f"(sd) : "f"(v));
    rsd = rcp(rbf(sd));
}
__device__ __forceinline__ uint32_t ln_apply(float xa, float xb, float mean, float rsd, uint32_t scale1, uint32_t shift) {
    uint32_t p = pack2(xa - mean, xb - mean);
    p = pack2(blo(p) * rsd, bhi(p) * rsd);
    p = pack2(blo(p) * blo(scale1), bhi(p) * bhi(scale1));
    return pack2(blo(p) + blo(shift), bhi(p) + bhi(shift));
}

__device__ __forceinline__ void load_box32(uint32_t box, const __nv_bfloat16* src, int ld, int lane) {
    const __nv_bfloat16* p = src + (lane >> 2) * ld + (lane & 3) * 8;
    const uint32_t d = box + (lane >> 2) * 64 + (((lane & 3) ^ (lane >> 3)) << 4);
#pragma unroll
    for (int i = 0; i < 8; i++)
        asm volatile("cp.async.cg.shared.global [%0], [%1], 16;" ::"r"(d + i * 512), "l"(p + (size_t)(8 * i) * ld) : "memory");
}

__device__ __forceinline__ void gemv32(uint32_t box, uint32_t vp, float* red, int lane) {
    const int r = lane & 7, mhi = (lane >> 3) & 1, khi = lane >> 4, tig = lane & 3, g = lane >> 2;
    float c[2][2][4] = {};
#pragma unroll
    for (int s = 0; s < 4; s++) {
        uint32_t b0 = __shfl_sync(0xffffffffu, vp, 8 * s + tig), b1 = __shfl_sync(0xffffffffu, vp, 8 * s + 4 + tig);
        const int row = 16 * s + 8 * khi + r;
#pragma unroll
        for (int i = 0; i < 2; i++) {
            uint32_t a[4];
            ldsm4t(box + row * 64 + (((2 * i + mhi) ^ (r >> 1)) << 4), a);
            mma16816(c[i][s & 1], a, b0, b1);
        }
    }
    const float v0 = (tig & 1) ? c[0][0][2] + c[0][1][2] : c[0][0][0] + c[0][1][0];
    const float v1 = (tig & 1) ? c[1][0][2] + c[1][1][2] : c[1][0][0] + c[1][1][0];
    red[8 * tig + g] = (tig & 2) ? v1 : v0;
}
__device__ __forceinline__ float sum9(const float* p) {
    return (((p[0] + p[80]) + (p[160] + p[240])) + ((p[320] + p[400]) + (p[480] + p[560]))) + p[640];
}

template <int KROWS>
__device__ __forceinline__ void load_frags64(uint32_t box, uint32_t (&a)[(KROWS + 15) / 16][4][4], int lane) {
    const int r = lane & 7, mhi = (lane >> 3) & 1, khi = lane >> 4;
#pragma unroll
    for (int s = 0; s < (KROWS + 15) / 16; s++) {
        int row = 16 * s + 8 * khi + r;
        if (16 * s + 16 > KROWS && row >= KROWS) row = 16 * s + (r & 3);
#pragma unroll
        for (int i = 0; i < 4; i++) ldsm4t(box + row * 128 + (((2 * i + mhi) ^ (row & 7)) << 4), a[s][i]);
    }
}
template <int KS>
__device__ __forceinline__ void gemv64_publish(const uint32_t (&a)[KS][4][4], const uint32_t (&b)[KS][2], uint32_t* p,
                                               int tig, uint32_t tag) {
    float c[4][4] = {};
#pragma unroll
    for (int s = 0; s < KS; s++)
#pragma unroll
        for (int i = 0; i < 4; i++) mma16816(c[i], a[s][i], b[s][0], b[s][1]);
    const float v0 = (tig & 2) ? ((tig & 1) ? c[3][0] : c[2][0]) : ((tig & 1) ? c[1][0] : c[0][0]);
    const float v1 = (tig & 2) ? ((tig & 1) ? c[3][2] : c[2][2]) : ((tig & 1) ? c[1][2] : c[0][2]);
    stg1(p, tagw(v0, tag));
    stg1(p + NW * 8, tagw(v1, tag));
}

__device__ __forceinline__ void reduce128(const uint32_t* src, int lane, uint32_t tag, float (&s)[4]) {
    uint4 v[8];
    uint32_t n = 0, bad;
#pragma unroll
    for (int i = 0; i < 8; i++) v[i] = make_uint4(0, 0, 0, 0);
    do {
#pragma unroll
        for (int i = 0; i < 8; i++) if (bad4(v[i], tag)) v[i] = ldg4(src + (lane + 32 * i) * 4);
        bad = 0;
#pragma unroll
        for (int i = 0; i < 8; i++) bad |= bad4(v[i], tag);
        spin_guard(n);
    } while (bad);
    __syncwarp();
#define SUM8(f) (((untag(v[0].f) + untag(v[1].f)) + (untag(v[2].f) + untag(v[3].f))) + ((untag(v[4].f) + untag(v[5].f)) + (untag(v[6].f) + untag(v[7].f))))
    s[0] = SUM8(x); s[1] = SUM8(y); s[2] = SUM8(z); s[3] = SUM8(w);
#undef SUM8
#pragma unroll
    for (int o = 2; o < 32; o <<= 1) {
#pragma unroll
        for (int j = 0; j < 4; j++) s[j] += __shfl_xor_sync(0xffffffffu, s[j], o);
    }
}

__device__ __forceinline__ int static_begin(int c) { return (NSTATIC * c) / NCTA; }
__device__ __forceinline__ void prefetch_map(const CUtensorMap* m) { asm volatile("prefetch.tensormap [%0];" ::"l"(m) : "memory"); }
__device__ __forceinline__ void prefetch_l2(const void* p, uint32_t bytes) {
    asm volatile("cp.async.bulk.prefetch.L2.global [%0], %1;" ::"l"(p), "r"(bytes) : "memory");
}

struct Ptrs { const __nv_bfloat16 *x, *c, *wmod, *wq, *wo, *gate, *up, *down; __nv_bfloat16* out; };

__global__ void __launch_bounds__(NTHREADS, 1)
fused_kernel(const __grid_constant__ Maps maps, const __grid_constant__ Ptrs ptr) {
    extern __shared__ __align__(1024) unsigned char smem[];
    const uint32_t sb = (uint32_t)__cvta_generic_to_shared(smem);
    const int tid = threadIdx.x, warp = tid >> 5, lane = tid & 31, cta = blockIdx.x;
    const uint32_t bars = sb + OFF_BAR;
    volatile int* ntot = reinterpret_cast<volatile int*>(smem + OFF_NTOT);
    const bool has_mod = cta >= MOD_C0, has_w = cta < NW;

    TL0(0);
    uint32_t xp = 0, cp = 0, epoch = 0;
    if (warp < NCW) {
        if (has_mod) load_box32(sb + OFF_WMOD + 4096 * warp, ptr.wmod + 64 * warp * (6 * DM) + 32 * (cta - MOD_C0), 6 * DM, lane);
        else         load_box32(sb + OFF_WQ + 4096 * warp, ptr.wq + 64 * warp * 4096 + 32 * cta, 4096, lane);
        asm volatile("ld.global.nc.u32 %0, [%1];" : "=r"(cp) : "l"(ptr.c + 2 * tid));
        asm volatile("ld.global.nc.u32 %0, [%1];" : "=r"(xp) : "l"(ptr.x + 2 * tid));
        if (warp == 0) {
            if (has_mod) stg1(g_mod + 32 * (cta - MOD_C0) + lane, 0);
            if (has_w) stg1(g_q + 32 * cta + lane, 0);
        }
    } else if (tid == 32 * W_PROD) {
        prefetch_map(&maps.k);
        prefetch_map(&maps.v);
    }
    if (warp != W_PROD) asm volatile("ld.relaxed.gpu.global.u32 %0, [%1];" : "=r"(epoch) : "l"(&g_epoch) : "memory");
    if (lane == 0) {
#pragma unroll
        for (int i = 0; i < 5; i++) {
            const int b = warp + 11 * i;
            mbar_init(bars + 8 * b, b < B_PRO ? 1 : 64);
        }
        if (warp == 0) { mbar_init(bars + 8 * (B_END - 1), 32); *ntot = 0x7fffffff; }
        asm volatile("fence.proxy.async.shared::cta;" ::: "memory");
    }
    static_assert(B_END == 56, "barrier init covers 0..55");
    __syncthreads();

    const int t0 = static_begin(cta), t1 = static_begin(cta + 1);
    const int head0 = t0 / TPH;
    const int n0 = min(t1, (head0 + 1) * TPH) - t0;
    const int n01 = t1 - t0;
    const int woff = (-n01) & (NAS - 1);
    const int cnt_pool = 32 * (NAS + has_w + (cta < NRED));

    if (warp == W_PROD) {
        if (lane == 0) {
            if (sb & 1023) __trap();
            uint64_t pol;
            asm volatile("createpolicy.fractional.L2::evict_first.b64 %0, 1.0;" : "=l"(pol));
            uint32_t hist[DMAX];
#pragma unroll
            for (int i = 0; i < DMAX; i++) hist[i] = bars + 8 * (B_PRO + (i < D_PRO ? D_PRO - 1 - i : 0));
#define BEGIN_ITEM(D, bar, par, bytes)                                      \
            do {                                                            \
                mbar_wait(hist[(D) - 1] & ~1u, hist[(D) - 1] & 1u);         \
                _Pragma("unroll") for (int i_ = DMAX - 1; i_ > 0; i_--) hist[i_] = hist[i_ - 1]; \
                hist[0] = (bar) | (par);                                    \
                mbar_expect((bar), (bytes));                                \
            } while (0)
            uint32_t phm = 0;
#define ISSUE_TILE(D, t, w)                                                 \
            do {                                                            \
                const uint32_t ph_ = (phm >> (w)) & 1u;                     \
                const uint32_t fb_ = bars + 16 * (w), dst_ = sb + OFF_SLOT0 + (((w) + NAS - NAP) & (NAS - 1)) * (2 * ITEM); \
                phm ^= 1u << (w);                                           \
                _Pragma("unroll") for (int kv_ = 0; kv_ < 2; kv_++) {       \
                    mbar_wait(fb_ + 8 * (B_EMPTY + kv_), ph_ ^ 1);          \
                    BEGIN_ITEM(D, fb_ + 8 * kv_, ph_, (uint32_t)ITEM);      \
                    tma2d(dst_ + kv_ * ITEM, kv_ ? &maps.v : &maps.k, 0, (t) * (2 * TILE), fb_ + 8 * kv_, pol); \
                }                                                           \
            } while (0)

#pragma unroll 1
            for (int i = 0; i < NAS; i++) ISSUE_TILE(D_PRO, t0 + i, (i + woff) & (NAS - 1));
            TL(16);
#pragma unroll 1
            for (int i = NAS; i < n01 - 1; i++) ISSUE_TILE(D_MAIN, t0 + i, (i + woff) & (NAS - 1));
            uint32_t tk = atomicAdd(&g_ticket, 1u);
            ISSUE_TILE(D_MAIN, t1 - 1, NAS - 1);
            TL(17);
            const int fcol = (36 * cta) & ~7;
            if (has_w) {
                prefetch_map(&maps.wo); prefetch_map(&maps.gate); prefetch_map(&maps.up); prefetch_map(&maps.down);
                prefetch_l2(ptr.wo + 32 * cta * DM, 32);
                prefetch_l2(ptr.wo + (32 * cta + 31) * DM, 32);
                prefetch_l2(ptr.down + 36 * cta * DM, 32);
                prefetch_l2(ptr.down + (36 * cta + 35) * DM, 32);
#pragma unroll 1
                for (int r = 0; r < DM; r += 115) { prefetch_l2(ptr.gate + r * FF + fcol, 32); prefetch_l2(ptr.up + r * FF + fcol, 32); }
            }
            int n = 0, w = 0;
#pragma unroll 1
            while (tk < (uint32_t)NPOOL) {
                const uint32_t nx = atomicAdd(&g_ticket, 1u);
                ISSUE_TILE(D_POOL, NSTATIC + (int)tk, w);
                n++;
                if (++w == NAP) w = 0;
                tk = nx;
            }
            *ntot = n;
            TL(18);
            if (has_w) {
#pragma unroll 1
                for (int i = 0; i < 5; i++) {
                    const uint32_t bar = bars + 8 * (B_WO + i);
                    BEGIN_ITEM(D_TAIL, bar, 0u, i < 4 ? 8192u : 4096u);
                    tma2d(sb + OFF_WO + 8192 * i, &maps.wo, 128 * i, 32 * cta, bar, pol);
                    if (i < 4) tma2d(sb + OFF_WO + 8192 * i + 4096, &maps.wo, 128 * i + 64, 32 * cta, bar, pol);
                }
                TL(19);
#pragma unroll 1
                for (int i = 2 * NAP; i < 2 * NAS; i++) mbar_wait(bars + 8 * (B_EMPTY + i), ((phm >> (i >> 1)) & 1u) ^ 1);
#pragma unroll 1
                for (int i = 0; i < 9; i++) {
                    const uint32_t bar = bars + 8 * (B_GU + i);
                    BEGIN_ITEM(D_TAIL, bar, 0u, 10240u);
                    tma2d(sb + OFF_GATE + 5120 * i, &maps.gate, fcol, 64 * i, bar, pol);
                    tma2d(sb + OFF_UP + 5120 * i, &maps.up, fcol, 64 * i, bar, pol);
                }
                TL(20);
#pragma unroll 1
                for (int i = 0; i < 2 * NAP; i++) mbar_wait(bars + 8 * (B_EMPTY + i), ((phm >> (i >> 1)) & 1u) ^ 1);
#pragma unroll 1
                for (int i = 0; i < 5; i++) {
                    const uint32_t bar = bars + 8 * (B_DOWN + i);
                    BEGIN_ITEM(D_TAIL, bar, 0u, i < 4 ? 9216u : 4608u);
                    tma2d(sb + OFF_DOWN + 10240 * i, &maps.down, 128 * i, 36 * cta, bar, pol);
                    if (i < 4) tma2d(sb + OFF_DOWN + 10240 * i + 5120, &maps.down, 128 * i + 64, 36 * cta, bar, pol);
                }
                TL(21);
            }
        }
        return;
    }

    const uint32_t tag = epoch >= 3u ? 1u : epoch + 1u;

    if (warp == W_RED) {
        if (cta < NRED) {
            const int col = 8 * cta + 4 * (lane & 1);
            bar_sync(3, cnt_pool);
            if (lane < 2) stg4(g_x1 + col, 0, 0, 0, 0);
            const uint2 xq = *reinterpret_cast<const uint2*>(ptr.x + col);
            uint4 ga, gb;
            uint32_t n = 0;
            do { ga = ldg4(g_mod + 2 * DM + col); gb = ldg4(g_mod + 5 * DM + col); spin_guard(n); } while (bad4(ga, tag) | bad4(gb, tag));
            bar_sync(4, 32 * (NCW + 1));
            float s[4];
            reduce128(g_y + cta * (NW * 8), lane, tag, s);
            uint32_t p0 = pack2(s[0], s[1]), p1 = pack2(s[2], s[3]);
            p0 = pack2(untag(ga.x) * blo(p0), untag(ga.y) * bhi(p0));
            p1 = pack2(untag(ga.z) * blo(p1), untag(ga.w) * bhi(p1));
            const uint32_t x0 = pack2(blo(xq.x) + blo(p0), bhi(xq.x) + bhi(p0)), x1 = pack2(blo(xq.y) + blo(p1), bhi(xq.y) + bhi(p1));
            if (lane < 2) stg4(g_x1 + col, (x0 << 16) | tag, (x0 & 0xffff0000u) | tag, (x1 << 16) | tag, (x1 & 0xffff0000u) | tag);
            if (lane == 0) TL(24);
            mbar_wait(bars + 8 * (B_DOWN + 2), 0);
            reduce128(g_z + cta * (NW * 8), lane, tag, s);
            p0 = pack2(s[0], s[1]); p1 = pack2(s[2], s[3]);
            p0 = pack2(untag(gb.x) * blo(p0), untag(gb.y) * bhi(p0));
            p1 = pack2(untag(gb.z) * blo(p1), untag(gb.w) * bhi(p1));
            if (lane < 2)
                *reinterpret_cast<uint2*>(ptr.out + col) =
                    make_uint2(pack2(blo(x0) + blo(p0), bhi(x0) + bhi(p0)), pack2(blo(x1) + blo(p1), bhi(x1) + bhi(p1)));
            if (cta == 0 && lane == 0) { g_ticket = 0; g_epoch = tag; }
            if (lane == 0) TL(25);
        }
        return;
    }

    float* red = reinterpret_cast<float*>(smem + OFF_RED);
    float* stat = reinterpret_cast<float*>(smem + OFF_STAT);
    const int g = lane >> 2, tig = lane & 3;
    uint32_t cb1 = 0, sbp = 0;
    {
        const uint32_t pbar = bars + 8 * (B_PRO + (warp >> 1));
        const bool both = has_mod && has_w;
        if (!both) asm volatile("cp.async.mbarrier.arrive.noinc.shared::cta.b64 [%0];" ::"r"(pbar) : "memory");
        const float xa = blo(xp), xb = bhi(xp);
        ln_stats_part(xa, xb, stat, warp, lane);
        if (has_mod) {
            const float ca = blo(cp), cb = bhi(cp);
            const uint32_t vp = pack2(ca * rcp(1.0f + ex2(-1.4426950408889634f * ca)), cb * rcp(1.0f + ex2(-1.4426950408889634f * cb)));
            asm volatile("cp.async.wait_all;" ::: "memory");
            __syncwarp();
            if (both) {
                load_box32(sb + OFF_WQ + 4096 * warp, ptr.wq + 64 * warp * 4096 + 32 * cta, 4096, lane);
                asm volatile("cp.async.mbarrier.arrive.noinc.shared::cta.b64 [%0];" ::"r"(pbar) : "memory");
            }
            gemv32(sb + OFF_WMOD + 4096 * warp, vp, red + 80 * warp, lane);
        }
        bar_sync(2, 32 * NCW);
        if (has_mod && warp == 0) stg1(g_mod + 32 * (cta - MOD_C0) + lane, __float_as_uint(rbf(sum9(red + lane))) | tag);
        TL0(1);
        if (has_w) {
            float mean, rsd;
            ln_stats_fin(stat, mean, rsd);
            uint2 sa, ca;
            uint32_t n = 0;
            do { sa = ldg2(g_mod + 2 * tid); ca = ldg2(g_mod + DM + 2 * tid); spin_guard(n); } while (bad2(sa, tag) | bad2(ca, tag));
            TL0(2);
            const uint32_t hp = ln_apply(xa, xb, mean, rsd, pack2(1.0f + untag(ca.x), 1.0f + untag(ca.y)), __byte_perm(sa.x, sa.y, 0x7632));
            asm volatile("cp.async.wait_all;" ::: "memory");
            __syncwarp();
            gemv32(sb + OFF_WQ + 4096 * warp, hp, red + 720 + 80 * warp, lane);
            bar_sync(2, 32 * NCW);
            if (warp == 0) stg1(g_q + 32 * cta + lane, __float_as_uint(rbf(sum9(red + 720 + lane))) | tag);
            TL0(3);
        }
        {
            const int seg = tid >> 6;
            const int hd = seg == 0 ? head0 : seg == 1 ? head0 + 1 : HKV - 1;
            uint4 v = make_uint4(tag, tag, tag, tag);
            uint2 s2 = make_uint2(0, 0), c2 = s2;
            uint32_t n = 0;
            do {
                if (tid < 192) v = ldg4(g_q + 256 * hd + 4 * (tid & 63));
                if (bad2(s2, tag) | bad2(c2, tag)) { s2 = ldg2(g_mod + 3 * DM + 2 * tid); c2 = ldg2(g_mod + 4 * DM + 2 * tid); }
                spin_guard(n);
            } while (bad4(v, tag) | bad2(s2, tag) | bad2(c2, tag));
            if (tid < 192)
                *reinterpret_cast<uint2*>(smem + OFF_Q + 8 * tid) = make_uint2(__byte_perm(v.x, v.y, 0x7632), __byte_perm(v.z, v.w, 0x7632));
            sbp = __byte_perm(s2.x, s2.y, 0x7632);
            cb1 = pack2(1.0f + untag(c2.x), 1.0f + untag(c2.y));
        }
        asm volatile("fence.proxy.async.shared::cta;" ::: "memory");
        bar_sync(2, 32 * NCW);
        TL0(4);
    }
    uint32_t* const yslot = g_y + ((8 * warp + 2 * tig) * NW + cta) * 8 + g;
    uint32_t* const zslot = g_z + ((8 * warp + 2 * tig) * NW + cta) * 8 + g;

    if (warp < NAS) {
        const int r = lane & 7, var = r >> 2;
        const uint32_t kofs = (r + 8 * ((lane >> 3) & 1)) * 256, kx = (lane >> 4) ^ var ^ (2 * (r & 3));
        const uint32_t vofs = (r + 8 * (lane >> 4)) * 256, vx = ((lane >> 3) & 1) ^ var ^ (2 * (r & 3));
        const float bias = (tig == (g >> 2)) ? 0.f : -INFINITY;
        float* stage = reinterpret_cast<float*>(smem + OFF_STAGE);
        const uint32_t slot = sb + OFF_SLOT0 + ((warp + NAS - NAP) & (NAS - 1)) * (2 * ITEM);
        const uint32_t kb = slot + kofs, vb = slot + ITEM + vofs;
        const uint32_t kfull = bars + 16 * warp, kempty = kfull + 8 * B_EMPTY;
        int i = (warp - woff) & (NAS - 1);
        uint32_t ph = 0;
#pragma unroll 1
        for (int seg = 0; seg < 3; seg++) {
            if (seg == 1 && n01 == n0) continue;
            if (seg == 2) {
                if (has_w) { stg1(yslot, 0); stg1(yslot + NW * 8, 0); stg1(zslot, 0); stg1(zslot + NW * 8, 0); }
                if (warp >= NAP) break;
                if (tid < 128) {
                    stg2(g_part + (cta * 3 + 2) * 256 + 2 * tid, 0, 0);
                    if ((tid & 63) == 0) stg4(g_ml + ((cta * 3 + 2) * 2 + (tid >> 6)) * 4, 0, 0, 0, 0);
                }
                i = warp;
            }
            uint32_t qf[8][2];
            {
                const uint32_t* qs = reinterpret_cast<const uint32_t*>(smem + OFF_Q) + 128 * seg + 64 * (g & 1) + tig;
                const int qv = (g >> 1) & 1;
#pragma unroll
                for (int s = 0; s < 8; s++) { qf[s][0] = qs[8 * s + 4 * qv]; qf[s][1] = qs[8 * s + 4 * (qv ^ 1)]; }
            }
            float o[8][4] = {};
            float m0 = NEG_BIG, m1 = NEG_BIG, l0 = 0.f, l1 = 0.f;
            const int end = seg == 0 ? n0 : n01;
            const int nw = seg == 2 ? NAP : NAS;
#pragma unroll 1
            for (;; i += nw) {
                if (seg < 2) {
                    if (i >= end) break;
                    mbar_wait(kfull, ph);
                } else {
                    bool stop = false;
                    uint32_t n = 0;
                    while (!mbar_test(kfull, ph)) {
                        if (i >= *ntot) { stop = true; break; }
                        spin_guard(n);
                    }
                    if (__any_sync(0xffffffffu, stop)) break;
                }
                float s[2][2][4] = {};
#pragma unroll
                for (int st = 0; st < 8; st++) {
#pragma unroll
                    for (int mt = 0; mt < 2; mt++) {
                        uint32_t a[4];
                        ldsm4(kb + mt * 4096 + (st >> 2) * 128 + (((2 * (st & 3)) ^ (st >> 2) ^ kx) << 4), a);
                        mma16816(s[mt][st & 1], a, qf[st][0], qf[st][1]);
                    }
                }
                __syncwarp();
                if (lane == 0) mbar_arrive(kempty);
                float t[2][4];
#pragma unroll
                for (int mt = 0; mt < 2; mt++)
#pragma unroll
                    for (int j = 0; j < 4; j += 2) {
                        uint32_t p = pack2(s[mt][0][j] + s[mt][1][j], s[mt][0][j + 1] + s[mt][1][j + 1]);
                        p = pack2(blo(p) * 0.08838834764831845f, bhi(p) * 0.08838834764831845f);
                        t[mt][j] = fmaf(blo(p), 1.4426950408889634f, bias);
                        t[mt][j + 1] = fmaf(bhi(p), 1.4426950408889634f, bias);
                    }
                float x0 = fmaxf(fmaxf(t[0][0], t[0][2]), fmaxf(t[1][0], t[1][2]));
                float x1 = fmaxf(fmaxf(t[0][1], t[0][3]), fmaxf(t[1][1], t[1][3]));
                if (__any_sync(0xffffffffu, x0 > m0 || x1 > m1)) {
#pragma unroll
                    for (int d = 16; d; d >>= 1) {
                        x0 = fmaxf(x0, __shfl_xor_sync(0xffffffffu, x0, d));
                        x1 = fmaxf(x1, __shfl_xor_sync(0xffffffffu, x1, d));
                    }
                    x0 = fmaxf(x0, m0); x1 = fmaxf(x1, m1);
                    const float a0 = ex2(m0 - x0), a1 = ex2(m1 - x1);
                    m0 = x0; m1 = x1;
                    l0 *= a0; l1 *= a1;
#pragma unroll
                    for (int j = 0; j < 8; j++) { o[j][0] *= a0; o[j][1] *= a1; o[j][2] *= a0; o[j][3] *= a1; }
                }
                uint32_t pb[2][2];
#pragma unroll
                for (int mt = 0; mt < 2; mt++) {
                    const float p0 = ex2(t[mt][0] - m0), p1 = ex2(t[mt][1] - m1), p2 = ex2(t[mt][2] - m0), p3 = ex2(t[mt][3] - m1);
                    l0 += p0 + p2; l1 += p1 + p3;
                    pb[mt][0] = movmat(pack2(p0, p1));
                    pb[mt][1] = movmat(pack2(p2, p3));
                }
                mbar_wait(kfull + 8, ph);
#pragma unroll
                for (int mt = 0; mt < 2; mt++) {
#pragma unroll
                    for (int j = 0; j < 8; j++) {
                        uint32_t a[4];
                        ldsm4t(vb + mt * 4096 + (j >> 2) * 128 + (((2 * (j & 3)) ^ (j >> 2) ^ vx) << 4), a);
                        mma16816(o[j], a, pb[mt][0], pb[mt][1]);
                    }
                }
                __syncwarp();
                if (lane == 0) mbar_arrive(kempty + 8);
                ph ^= 1;
            }
            if (seg == 2) TL0(5);
            l0 += __shfl_xor_sync(0xffffffffu, l0, 17); l1 += __shfl_xor_sync(0xffffffffu, l1, 17);
            float* sw = stage + 260 * warp;
#pragma unroll
            for (int j = 0; j < 8; j++) {
                const float u0 = o[j][0] + __shfl_xor_sync(0xffffffffu, o[j][2], 1);
                const float u1 = o[j][1] + __shfl_xor_sync(0xffffffffu, o[j][3], 1);
                if (tig < 2) { sw[16 * j + 8 * tig + g] = u0; sw[128 + 16 * j + 8 * tig + g] = u1; }
                if (j == 2 || j == 5) {
                    l0 += __shfl_xor_sync(0xffffffffu, l0, j == 2 ? 4 : 8);
                    l1 += __shfl_xor_sync(0xffffffffu, l1, j == 2 ? 4 : 8);
                }
            }
            if (lane == 0) *reinterpret_cast<float4*>(sw + 256) = make_float4(m0, l0, m1, l1);
            bar_sync(1, 32 * nw);
            if (tid < 128) {
                const int h = tid >> 6;
                float2 ml[NAS], ov[NAS];
                float M = NEG_BIG;
#pragma unroll
                for (int w = 0; w < NAS; w++) {
                    ml[w] = make_float2(NEG_BIG, 0.f); ov[w] = make_float2(0.f, 0.f);
                    if (w < NAP || seg < 2) {
                        ml[w] = *reinterpret_cast<const float2*>(stage + 260 * w + 256 + 2 * h);
                        ov[w] = *reinterpret_cast<const float2*>(stage + 260 * w + 2 * tid);
                    }
                    M = fmaxf(M, ml[w].x);
                }
                float a = 0.f, b = 0.f, L = 0.f;
#pragma unroll
                for (int w = 0; w < NAS; w++) {
                    const float e = ex2(ml[w].x - M);
                    a += e * ov[w].x; b += e * ov[w].y; L += e * ml[w].y;
                }
                stg2(g_part + (cta * 3 + seg) * 256 + 2 * tid, tagw(a, tag), tagw(b, tag));
                if ((tid & 63) == 0)
                    stg4(g_ml + ((cta * 3 + seg) * 2 + h) * 4, tagw(M, tag), (__float_as_uint(M) << 2) | tag, tagw(L, tag), tag);
            }
            if (seg < 2) { if (end == n01) bar_sync(3, cnt_pool); else bar_sync(1, 32 * NAS); }
        }
        TL0(6);
    } else if (has_w) {
        bar_sync(3, cnt_pool);
        stg1(yslot, 0); stg1(yslot + NW * 8, 0); stg1(zslot, 0); stg1(zslot + NW * 8, 0);
    }
    if (!has_w) return;

    if (warp >= NAP) {
        const int hq = cta >> 2, kvh = hq >> 1, h = hq & 1, u = tid - 32 * NAP;
        int rec0, n;
        if (kvh < HKV - 1) {
            int c_lo = (kvh * TPH * NCTA) / NSTATIC;
            while (static_begin(c_lo + 1) <= kvh * TPH) c_lo++;
            while (static_begin(c_lo) > kvh * TPH) c_lo--;
            const int c = c_lo + (u >> 3), b = static_begin(c);
            n = b < (kvh + 1) * TPH ? 1 : 0;
            rec0 = (c * 3 + (b / TPH == kvh ? 0 : 1)) * 2 + h;
        } else {
            rec0 = ((u >> 3) * 3 + 2) * 2 + h;
            n = NCTA - (u >> 3);
            uint32_t spin = 0;
            while (*ntot == 0x7fffffff) { __nanosleep(100); spin_guard(spin); }
        }
        const uint32_t* po = g_part + rec0 * 128 + 32 * (cta & 3) + 4 * (u & 7);
        const uint32_t* pm = g_ml + rec0 * 4;
        uint4 ov[9], ml[9];
#pragma unroll
        for (int k = 0; k < 9; k++) {
            const uint32_t w = 16 * k < n ? 0 : tag;
            ov[k] = make_uint4(w, w, w, w);
            ml[k] = make_uint4(tagw(NEG_BIG, tag), w, w, w);
        }
        uint32_t bad, spin = 0;
        do {
#pragma unroll
            for (int k = 0; k < 9; k++)
                if (bad4(ov[k], tag) | bad4(ml[k], tag)) { ov[k] = ldg4(po + k * (96 * 128)); ml[k] = ldg4(pm + k * (96 * 4)); }
            bad = 0;
#pragma unroll
            for (int k = 0; k < 9; k++) bad |= bad4(ov[k], tag) | bad4(ml[k], tag);
            if (bad && kvh < HKV - 1) __nanosleep(200);
            spin_guard(spin);
        } while (bad);
        __syncwarp();
        float mk[9], M = NEG_BIG;
#pragma unroll
        for (int k = 0; k < 9; k++) { mk[k] = __uint_as_float((ml[k].x & ~3u) | ((ml[k].y >> 2) & 3u)); M = fmaxf(M, mk[k]); }
        M = fmaxf(M, __shfl_xor_sync(0xffffffffu, M, 8));
        M = fmaxf(M, __shfl_xor_sync(0xffffffffu, M, 16));
        float a[5] = {};
#pragma unroll
        for (int k = 0; k < 9; k++) {
            const float e = ex2(mk[k] - M);
            a[0] += e * untag(ov[k].x); a[1] += e * untag(ov[k].y); a[2] += e * untag(ov[k].z); a[3] += e * untag(ov[k].w);
            a[4] += e * untag(ml[k].z);
        }
#pragma unroll
        for (int j = 0; j < 5; j++) a[j] += __shfl_xor_sync(0xffffffffu, a[j], 8);
#pragma unroll
        for (int j = 0; j < 5; j++) a[j] += __shfl_xor_sync(0xffffffffu, a[j], 16);
        if (lane < 8) *reinterpret_cast<float4*>(red + 80 * (warp - NAP) + 4 * lane) = make_float4(a[0], a[1], a[2], a[3]);
        if (lane == 0) *reinterpret_cast<float2*>(red + 320 + 2 * (warp - NAP)) = make_float2(M, a[4]);
        if (tid == 256) TL(13);
    }
    {
        uint32_t wa[2][4][4], ob[2][2];
        mbar_wait(bars + 8 * (B_WO + (warp >> 1)), 0);
        load_frags64<32>(sb + OFF_WO + 4096 * warp, wa, lane);
        bar_sync(4, 32 * (NCW + (cta < NRED)));
        TL0(7);
        const float4 s0 = *reinterpret_cast<const float4*>(red + 320), s1 = *reinterpret_cast<const float4*>(red + 324);
        const float MM = fmaxf(fmaxf(s0.x, s0.z), fmaxf(s1.x, s1.z));
        const float e0 = ex2(s0.x - MM), e1 = ex2(s0.z - MM), e2 = ex2(s1.x - MM), e3 = ex2(s1.z - MM);
        const float inv = rcp((e0 * s0.y + e1 * s0.w) + (e2 * s1.y + e3 * s1.w));
#pragma unroll
        for (int j = 0; j < 4; j++) {
            const float* p = red + 8 * j + 2 * tig;
            const float2 a = *reinterpret_cast<const float2*>(p), b = *reinterpret_cast<const float2*>(p + 80),
                         c = *reinterpret_cast<const float2*>(p + 160), d = *reinterpret_cast<const float2*>(p + 240);
            ob[j >> 1][j & 1] = pack2(((e0 * a.x + e1 * b.x) + (e2 * c.x + e3 * d.x)) * inv, ((e0 * a.y + e1 * b.y) + (e2 * c.y + e3 * d.y)) * inv);
        }
        gemv64_publish<2>(wa, ob, yslot, tig, tag);
        TL0(8);
    }

    {
        uint32_t ga[4][5][4];
        {
            const int r = lane & 7, mhi = (lane >> 3) & 1, khi = lane >> 4;
            const uint32_t box = sb + (mhi ? OFF_UP : OFF_GATE) + 5120 * warp + (8 * khi + r) * 80;
            mbar_wait(bars + 8 * (B_GU + warp), 0);
#pragma unroll
            for (int s = 0; s < 4; s++)
#pragma unroll
                for (int i = 0; i < 5; i++) ldsm4t(box + s * 1280 + 16 * i, ga[s][i]);
        }
        if (tid == 256) TL(14);
        uint2 xv;
        uint32_t n = 0;
        do { xv = ldg2(g_x1 + 2 * tid); spin_guard(n); } while (bad2(xv, tag));
        __syncwarp();
        TL0(15);
        const float xa = untag(xv.x), xb = untag(xv.y);
        ln_stats_part(xa, xb, stat + 20, warp, lane);
        bar_sync(2, 32 * NCW);
        TL0(9);
        float mean, rsd;
        ln_stats_fin(stat + 20, mean, rsd);
        const uint32_t hp = ln_apply(xa, xb, mean, rsd, cb1, sbp);
        float c[5][4] = {};
#pragma unroll
        for (int s = 0; s < 4; s++) {
            const uint32_t b0 = __shfl_sync(0xffffffffu, hp, 8 * s + tig), b1 = __shfl_sync(0xffffffffu, hp, 8 * s + 4 + tig);
#pragma unroll
            for (int i = 0; i < 5; i++) mma16816(c[i], ga[s][i], b0, b1);
        }
        float* rw = red + 720 + 80 * warp;
        if (tig < 2) {
#pragma unroll
            for (int i = 0; i < 5; i++) rw[40 * tig + 8 * i + g] = tig ? c[i][2] : c[i][0];
        }
    }
    uint32_t da[3][4][4], hb[3][2];
    const uint32_t dbar = bars + 8 * (B_DOWN + (warp >> 1));
    const bool early = __all_sync(0xffffffffu, mbar_test(dbar, 0));
    if (early) load_frags64<36>(sb + OFF_DOWN + 5120 * warp, da, lane);
    bar_sync(2, 32 * NCW);
    TL0(10);
    {
        uint32_t pr = 0;
        if (lane < 18) {
            const float* q = red + 720 + ((36 * cta) & 7) + 2 * lane;
            float2 gv[NCW], uv[NCW];
#pragma unroll
            for (int w = 0; w < NCW; w++) {
                gv[w] = *reinterpret_cast<const float2*>(q + 80 * w);
                uv[w] = *reinterpret_cast<const float2*>(q + 80 * w + 40);
            }
#define SUM9(v, f) ((((v[0].f + v[1].f) + (v[2].f + v[3].f)) + ((v[4].f + v[5].f) + (v[6].f + v[7].f))) + v[8].f)
            const uint32_t gp = pack2(SUM9(gv, x), SUM9(gv, y)), up = pack2(SUM9(uv, x), SUM9(uv, y));
#undef SUM9
            pr = pack2(blo(gp) * blo(up), bhi(gp) * bhi(up));
        }
#pragma unroll
        for (int s = 0; s < 3; s++) {
            hb[s][0] = __shfl_sync(0xffffffffu, pr, 8 * s + tig);
            hb[s][1] = s < 2 ? __shfl_sync(0xffffffffu, pr, 8 * s + 4 + tig) : 0u;
        }
    }
    if (!early) {
        mbar_wait(dbar, 0);
        load_frags64<36>(sb + OFF_DOWN + 5120 * warp, da, lane);
    }
    gemv64_publish<3>(da, hb, zslot, tig, tag);
}

typedef CUresult (*EncodeFn)(CUtensorMap*, CUtensorMapDataType, cuuint32_t, void*, const cuuint64_t*, const cuuint64_t*,
                             const cuuint32_t*, const cuuint32_t*, CUtensorMapInterleave, CUtensorMapSwizzle,
                             CUtensorMapL2promotion, CUtensorMapFloatOOBfill);

void make_map(EncodeFn enc, CUtensorMap* m, void* p, uint64_t cols, uint64_t rows, uint32_t bc, uint32_t br, CUtensorMapSwizzle sw) {
    cuuint64_t gd[2] = {cols, rows};
    cuuint64_t gs[1] = {cols * 2};
    cuuint32_t bd[2] = {bc, br};
    cuuint32_t es[2] = {1, 1};
    enc(m, CU_TENSOR_MAP_DATA_TYPE_BFLOAT16, 2, p, gd, gs, bd, es, CU_TENSOR_MAP_INTERLEAVE_NONE, sw,
        CU_TENSOR_MAP_L2_PROMOTION_NONE, CU_TENSOR_MAP_FLOAT_OOB_FILL_NONE);
}

}

extern "C" void kernel_launch(void* const* d_in, const int* in_sizes, int n_in, void* d_out, int out_size) {
    (void)in_sizes; (void)n_in; (void)out_size;
    EncodeFn enc = nullptr;
    cudaDriverEntryPointQueryResult qr;
    cudaGetDriverEntryPoint("cuTensorMapEncodeTiled", (void**)&enc, cudaEnableDefault, &qr);
    Maps maps;
    make_map(enc, &maps.k, d_in[1], 64, (uint64_t)HKV * SK * 2, 64, 2 * TILE, CU_TENSOR_MAP_SWIZZLE_128B);
    make_map(enc, &maps.v, d_in[2], 64, (uint64_t)HKV * SK * 2, 64, 2 * TILE, CU_TENSOR_MAP_SWIZZLE_128B);
    make_map(enc, &maps.wo, d_in[4], DM, 4096, 64, 32, CU_TENSOR_MAP_SWIZZLE_128B);
    make_map(enc, &maps.gate, d_in[6], FF, DM, 40, 64, CU_TENSOR_MAP_SWIZZLE_NONE);
    make_map(enc, &maps.up, d_in[7], FF, DM, 40, 64, CU_TENSOR_MAP_SWIZZLE_NONE);
    make_map(enc, &maps.down, d_in[8], DM, FF, 64, 36, CU_TENSOR_MAP_SWIZZLE_128B);
    cudaFuncSetAttribute(fused_kernel, cudaFuncAttributeMaxDynamicSharedMemorySize, SMEM_BYTES);
    typedef const __nv_bfloat16* P;
    const Ptrs ptr = {(P)d_in[0], (P)d_in[9], (P)d_in[10], (P)d_in[3], (P)d_in[4], (P)d_in[6], (P)d_in[7], (P)d_in[8], (__nv_bfloat16*)d_out};
    fused_kernel<<<NCTA, NTHREADS, SMEM_BYTES, cudaStreamPerThread>>>(maps, ptr);
}
```

```cpp
#include <cuda_runtime.h>
#include <cuda_bf16.h>
#include <cuda.h>
#include <stdint.h>

namespace {

constexpr int DM = 576;
constexpr int SK = 65536;
constexpr int HKV = 16;
constexpr int FF = 4608;
constexpr int NCTA = 132;
constexpr int NQ = 128;
constexpr int MOD_C0 = 24;
constexpr int NRED = 72;
constexpr int C_X = 96, C_P = 120, C_E = 128;
constexpr int NY = C_X + (C_E - C_P);
constexpr int FX0 = 32 * NCTA;
static_assert(FX0 + 16 * (C_P - C_X) == FF && 40 * C_X == 256 * (HKV - 1), "weight split");

constexpr int TILE = 32;
constexpr int TPH = SK / TILE;
constexpr int NSTATIC = (HKV - 1) * TPH;
constexpr int NPOOL = TPH;
constexpr int ITEM = TILE * 256;

#define D_MAIN 6
#define D_POOL 5
#define D_TAIL 4
#define BOOST 0
#define D_WO D_TAIL
#define X1_GATE 6
#define Y_GATE 0
#define GU_PROMO 2
#define TIMED 1
#define T_LEAD 1.9f
#define T_SPEED 1.025f
#define T_DOWN 1.0f
#define T_WO 1.0f
#define D_CAP 6
#define BURST 0
#define WO_EARLY 0
#define XREP 4
#define D_DOWN D_TAIL
#define D_PRO 5
constexpr int DMAX = 8;

constexpr int NCW = 9;
constexpr int NAS = 8;
constexpr int NAP = 5;
constexpr int W_PROD = 9, W_RED = 10;
constexpr int NTHREADS = 12 * 32;

constexpr int OFF_WMOD = 0;
constexpr int OFF_WQ = 9 * 4096;
constexpr int OFF_WO = 0;
constexpr int OFF_GATEX = 0;
constexpr int OFF_UPX = 9 * 2048;
constexpr int OFF_GATE = 40 * 1152;
constexpr int OFF_UP = OFF_GATE + 9 * 4096;
constexpr int OFF_SLOT0 = 18 * 4096;
constexpr int OFF_RING = OFF_SLOT0 + 2 * (NAS - NAP) * ITEM;
constexpr int OFF_DOWN = OFF_RING;
constexpr int OFF_BAR = OFF_RING + 2 * NAP * ITEM;
constexpr int OFF_STAGE = OFF_BAR + 512;
constexpr int OFF_RED = OFF_STAGE + NAS * 260 * 4;
constexpr int OFF_Q = OFF_RED + 9 * (80 + 96) * 4;
constexpr int OFF_STAT = OFF_Q + 3 * 256 * 2;
constexpr int OFF_VEC = OFF_STAT + 2 * 20 * 4;
constexpr int OFF_NTOT = OFF_VEC + 64 * 4;
constexpr int SMEM_BYTES = OFF_NTOT + 16;
static_assert(SMEM_BYTES <= 232448, "smem");
static_assert(OFF_UP + 9 * 4096 <= OFF_RING && OFF_GATE % 1024 == 0, "layout");

constexpr int B_EMPTY = 2 * NAS, B_WO = 4 * NAS, B_GU = B_WO + 5, B_DOWN = B_GU + 9, B_SDONE = B_DOWN + 6, B_PDONE = B_SDONE + 1,
              B_WMOD = B_PDONE + 1, B_WQ = B_WMOD + 5, B_END = B_WQ + 5;
static_assert(B_END <= 64, "barriers");

constexpr float NEG_BIG = -1.0e30f;
constexpr uint32_t SPIN_LIMIT = 1u << 22;

struct Maps { CUtensorMap wmod, wq, k, v, wo, gate, up, gatex, upx, down; };

__device__ uint32_t g_epoch;
__device__ uint32_t g_ticket;
__device__ __align__(128) uint32_t g_mod[6 * DM];
__device__ __align__(128) uint32_t g_q[4096];
__device__ __align__(128) uint32_t g_part[NCTA * 3 * 2 * 128];
__device__ __align__(128) uint32_t g_ml[3 * 2 * 144 * 4];
__device__ __align__(128) uint32_t g_y[NRED * NY * 8];
__device__ __align__(128) uint32_t g_x1[XREP * DM];
__device__ __align__(128) uint32_t g_z[NRED * NCTA * 8];

#define TLM(i)
#define TL(i)
#define TL0(i)

__device__ __forceinline__ void mbar_init(uint32_t b, uint32_t c) {
    asm volatile("mbarrier.init.shared::cta.b64 [%0], %1;" ::"r"(b), "r"(c) : "memory");
}
__device__ __forceinline__ void mbar_expect(uint32_t b, uint32_t bytes) {
    asm volatile("mbarrier.arrive.expect_tx.shared::cta.b64 _, [%0], %1;" ::"r"(b), "r"(bytes) : "memory");
}
__device__ __forceinline__ void mbar_arrive(uint32_t b) {
    asm volatile("mbarrier.arrive.shared::cta.b64 _, [%0];" ::"r"(b) : "memory");
}
__device__ __forceinline__ bool mbar_try(uint32_t b, uint32_t ph) {
    uint32_t ok;
    asm volatile("{\n.reg .pred p;\nmbarrier.try_wait.parity.shared::cta.b64 p, [%1], %2;\nselp.u32 %0, 1, 0, p;\n}"
                 : "=r"(ok) : "r"(b), "r"(ph) : "memory");
    return ok;
}
__device__ __forceinline__ bool mbar_test(uint32_t b, uint32_t ph) {
    uint32_t ok;
    asm volatile("{\n.reg .pred p;\nmbarrier.test_wait.parity.shared::cta.b64 p, [%1], %2;\nselp.u32 %0, 1, 0, p;\n}"
                 : "=r"(ok) : "r"(b), "r"(ph) : "memory");
    return ok;
}
__device__ __forceinline__ void mbar_wait(uint32_t b, uint32_t ph) {
    uint32_t n = 0;
    while (!mbar_try(b, ph)) { if (++n > SPIN_LIMIT) __trap(); }
}
__device__ __forceinline__ void tma2d(uint32_t dst, const CUtensorMap* m, int c0, int c1, uint32_t bar, uint64_t pol) {
    asm volatile("cp.async.bulk.tensor.2d.shared::cluster.global.mbarrier::complete_tx::bytes.L2::cache_hint "
                 "[%0], [%1, {%3, %4}], [%2], %5;"
                 ::"r"(dst), "l"(m), "r"(bar), "r"(c0), "r"(c1), "l"(pol) : "memory");
}
__device__ __forceinline__ void bar_sync(int id, int n) { asm volatile("bar.sync %0, %1;" ::"r"(id), "r"(n) : "memory"); }
__device__ __forceinline__ void ldsm4(uint32_t a, uint32_t (&r)[4]) {
    asm volatile("ldmatrix.sync.aligned.m8n8.x4.shared.b16 {%0,%1,%2,%3}, [%4];"
                 : "=r"(r[0]), "=r"(r[1]), "=r"(r[2]), "=r"(r[3]) : "r"(a) : "memory");
}
__device__ __forceinline__ void ldsm4t(uint32_t a, uint32_t (&r)[4]) {
    asm volatile("ldmatrix.sync.aligned.m8n8.x4.trans.shared.b16 {%0,%1,%2,%3}, [%4];"
                 : "=r"(r[0]), "=r"(r[1]), "=r"(r[2]), "=r"(r[3]) : "r"(a) : "memory");
}
__device__ __forceinline__ void mma16816(float (&c)[4], const uint32_t (&a)[4], uint32_t b0, uint32_t b1) {
    asm volatile("mma.sync.aligned.m16n8k16.row.col.f32.bf16.bf16.f32 {%0,%1,%2,%3}, {%4,%5,%6,%7}, {%8,%9}, {%0,%1,%2,%3};"
                 : "+f"(c[0]), "+f"(c[1]), "+f"(c[2]), "+f"(c[3])
                 : "r"(a[0]), "r"(a[1]), "r"(a[2]), "r"(a[3]), "r"(b0), "r"(b1));
}
__device__ __forceinline__ uint32_t movmat(uint32_t a) {
    uint32_t d; asm volatile("movmatrix.sync.aligned.m8n8.trans.b16 %0, %1;" : "=r"(d) : "r"(a)); return d;
}
__device__ __forceinline__ float ex2(float x) { float y; asm("ex2.approx.ftz.f32 %0, %1;" : "=f"(y) : "f"(x)); return y; }
__device__ __forceinline__ uint32_t pack2(float lo, float hi) {
    uint32_t r; asm("cvt.rn.bf16x2.f32 %0, %1, %2;" : "=r"(r) : "f"(hi), "f"(lo)); return r;
}
__device__ __forceinline__ float rbf(float x) { return __uint_as_float(pack2(0.f, x)); }
__device__ __forceinline__ float rcp(float x) { float y; asm("rcp.approx.ftz.f32 %0, %1;" : "=f"(y) : "f"(x)); return y; }
__device__ __forceinline__ float blo(uint32_t p) { return __uint_as_float(p << 16); }
__device__ __forceinline__ float bhi(uint32_t p) { return __uint_as_float(p & 0xffff0000u); }

__device__ __forceinline__ uint32_t tagw(float v, uint32_t tag) { return (__float_as_uint(v) & ~3u) | tag; }
__device__ __forceinline__ float untag(uint32_t w) { return __uint_as_float(w & ~3u); }
__device__ __forceinline__ void stg1(uint32_t* p, uint32_t a) {
    asm volatile("st.relaxed.gpu.global.u32 [%0], %1;" ::"l"(p), "r"(a) : "memory");
}
__device__ __forceinline__ void stg2(uint32_t* p, uint32_t a, uint32_t b) {
    asm volatile("st.relaxed.gpu.global.v2.u32 [%0], {%1,%2};" ::"l"(p), "r"(a), "r"(b) : "memory");
}
__device__ __forceinline__ void stg4(uint32_t* p, uint32_t a, uint32_t b, uint32_t c, uint32_t d) {
    asm volatile("st.relaxed.gpu.global.v4.u32 [%0], {%1,%2,%3,%4};" ::"l"(p), "r"(a), "r"(b), "r"(c), "r"(d) : "memory");
}
__device__ __forceinline__ void red1(uint32_t* p, uint32_t a) {
    asm volatile("red.relaxed.gpu.global.or.b32 [%0], %1;" ::"l"(p), "r"(a) : "memory");
}
__device__ __forceinline__ void red2(uint32_t* p, uint32_t a, uint32_t b) {
    asm volatile("{\n.reg .b64 t;\nmov.b64 t, {%1, %2};\nred.relaxed.gpu.global.or.b64 [%0], t;\n}" ::"l"(p), "r"(a), "r"(b) : "memory");
}
__device__ __forceinline__ uint32_t ldg1(const uint32_t* p) {
    uint32_t v; asm volatile("ld.relaxed.gpu.global.u32 %0, [%1];" : "=r"(v) : "l"(p) : "memory"); return v;
}
__device__ __forceinline__ uint2 ldg2(const uint32_t* p) {
    uint2 v; asm volatile("ld.relaxed.gpu.global.v2.u32 {%0,%1}, [%2];" : "=r"(v.x), "=r"(v.y) : "l"(p) : "memory"); return v;
}
__device__ __forceinline__ uint4 ldg4(const uint32_t* p) {
    uint4 v;
    asm volatile("ld.relaxed.gpu.global.v4.u32 {%0,%1,%2,%3}, [%4];" : "=r"(v.x), "=r"(v.y), "=r"(v.z), "=r"(v.w) : "l"(p) : "memory");
    return v;
}
__device__ __forceinline__ uint32_t bad2(uint2 v, uint32_t tag) { return ((v.x ^ tag) | (v.y ^ tag)) & 3u; }
__device__ __forceinline__ uint32_t bad4(uint4 v, uint32_t tag) {
    return ((v.x ^ tag) | (v.y ^ tag) | (v.z ^ tag) | (v.w ^ tag)) & 3u;
}
__device__ __forceinline__ uint32_t clk() { uint32_t c; asm volatile("mov.u32 %0, %%clock;" : "=r"(c)); return c; }
__device__ __forceinline__ void spin_guard(uint32_t& n) { if (++n > SPIN_LIMIT) __trap(); }

__device__ __forceinline__ void ln_stats_part(float a, float b, float* stat, int warp, int lane) {
    float s = a + b, q = a * a + b * b;
#pragma unroll
    for (int o = 16; o; o >>= 1) { s += __shfl_xor_sync(0xffffffffu, s, o); q += __shfl_xor_sync(0xffffffffu, q, o); }
    if (lane == 0) *reinterpret_cast<float2*>(stat + 2 * warp) = make_float2(s, q);
}
__device__ __forceinline__ void ln_stats_fin(const float* stat, float& mean, float& rsd) {
    const float4 a = *reinterpret_cast<const float4*>(stat), b = *reinterpret_cast<const float4*>(stat + 4),
                 c = *reinterpret_cast<const float4*>(stat + 8), d = *reinterpret_cast<const float4*>(stat + 12);
    const float2 e = *reinterpret_cast<const float2*>(stat + 16);
    const float mu = (((a.x + a.z) + (b.x + b.z)) + ((c.x + c.z) + (d.x + d.z)) + e.x) * (1.0f / DM);
    const float sq = (((a.y + a.w) + (b.y + b.w)) + ((c.y + c.w) + (d.y + d.w)) + e.y) * (1.0f / DM);
    mean = rbf(mu);
    const float v = rbf(rbf(fmaxf(fmaf(-mu, mu, sq), 0.f)) + 1e-5f);
    float sd;
    asm("sqrt.approx.ftz.f32 %0, %1;" : "=f"(sd) : "f"(v));
    rsd = rcp(rbf(sd));
}
__device__ __forceinline__ uint32_t ln_apply(float xa, float xb, float mean, float rsd, uint32_t scale1, uint32_t shift) {
    uint32_t p = pack2(xa - mean, xb - mean);
    p = pack2(blo(p) * rsd, bhi(p) * rsd);
    p = pack2(blo(p) * blo(scale1), bhi(p) * bhi(scale1));
    return pack2(blo(p) + blo(shift), bhi(p) + bhi(shift));
}

__device__ __forceinline__ void gemv32(uint32_t box, uint32_t vp, float* red, int lane) {
    const int r = lane & 7, mhi = (lane >> 3) & 1, khi = lane >> 4, tig = lane & 3, g = lane >> 2;
    float c[2][2][4] = {};
#pragma unroll
    for (int s = 0; s < 4; s++) {
        uint32_t b0 = __shfl_sync(0xffffffffu, vp, 8 * s + tig), b1 = __shfl_sync(0xffffffffu, vp, 8 * s + 4 + tig);
        const int row = 16 * s + 8 * khi + r;
#pragma unroll
        for (int i = 0; i < 2; i++) {
            uint32_t a[4];
            ldsm4t(box + row * 64 + (((2 * i + mhi) ^ (r >> 1)) << 4), a);
            mma16816(c[i][s & 1], a, b0, b1);
        }
    }
    const float v0 = (tig & 1) ? c[0][0][2] + c[0][1][2] : c[0][0][0] + c[0][1][0];
    const float v1 = (tig & 1) ? c[1][0][2] + c[1][1][2] : c[1][0][0] + c[1][1][0];
    red[8 * tig + g] = (tig & 2) ? v1 : v0;
}
__device__ __forceinline__ float sum9(const float* p) {
    return (((p[0] + p[80]) + (p[160] + p[240])) + ((p[320] + p[400]) + (p[480] + p[560]))) + p[640];
}

__device__ __forceinline__ void load_frags64(uint32_t base, int s, bool half, int w, int lane, uint32_t (&a)[4][4]) {
    const int r = lane & 7, mhi = (lane >> 3) & 1, khi = half ? 0 : lane >> 4;
    const int row = 16 * s + 8 * khi + r;
    const uint32_t line = base + (9 * row + w) * 128, x = mhi ^ ((row + w) & 7);
#pragma unroll
    for (int i = 0; i < 4; i++) ldsm4t(line + (((2 * i) ^ x) << 4), a[i]);
}
__device__ __forceinline__ void pick2(const float (&c)[4][4], int tig, float& v0, float& v1) {
    v0 = (tig & 2) ? ((tig & 1) ? c[3][0] : c[2][0]) : ((tig & 1) ? c[1][0] : c[0][0]);
    v1 = (tig & 2) ? ((tig & 1) ? c[3][2] : c[2][2]) : ((tig & 1) ? c[1][2] : c[0][2]);
}

template <int NP>
__device__ __forceinline__ void reduce_cols(const uint32_t* src, int half, int lane, uint32_t tag, float4* xch, float (&s)[4]) {
    constexpr int NL = (2 * NP + 63) / 64;
    uint4 v[NL];
    uint32_t n = 0, bad;
    const int t = 32 * half + lane;
    src += 4 * t;
#pragma unroll
    for (int i = 0; i < NL; i++) {
        const uint32_t w = (64 * i + 64 <= 2 * NP || 64 * i + t < 2 * NP) ? 0 : tag;
        v[i] = make_uint4(w, w, w, w);
    }
    do {
#pragma unroll
        for (int i = 0; i < NL; i++) if (bad4(v[i], tag)) v[i] = ldg4(src + 256 * i);
        bad = 0;
#pragma unroll
        for (int i = 0; i < NL; i++) bad |= bad4(v[i], tag);
        spin_guard(n);
    } while (bad);
    __syncwarp();
    if (NP == NY) TLM(30); else TLM(31);
#define SUM4(f) ((untag(v[0].f) + untag(v[1].f)) + (untag(v[2].f) + untag(v[3].f))) + (NL > 4 ? untag(v[NL - 1].f) : 0.f)
    s[0] = SUM4(x); s[1] = SUM4(y); s[2] = SUM4(z); s[3] = SUM4(w);
#undef SUM4
#pragma unroll
    for (int o = 2; o < 32; o <<= 1) {
#pragma unroll
        for (int j = 0; j < 4; j++) s[j] += __shfl_xor_sync(0xffffffffu, s[j], o);
    }
    if (half && lane < 2) xch[lane] = make_float4(s[0], s[1], s[2], s[3]);
    bar_sync(5, 64);
    const float4 o = xch[lane & 1];
    s[0] += o.x; s[1] += o.y; s[2] += o.z; s[3] += o.w;
}

__device__ __forceinline__ int static_begin(int c) { return (NSTATIC * c) / NCTA; }
__device__ __forceinline__ void prefetch_map(const CUtensorMap* m) { asm volatile("prefetch.tensormap [%0];" ::"l"(m) : "memory"); }

struct Ptrs { const __nv_bfloat16 *k, *x, *c; __nv_bfloat16* out; };

__global__ void __launch_bounds__(NTHREADS, 1)
fused_kernel(const __grid_constant__ Ptrs ptr, const __grid_constant__ Maps maps) {
    extern __shared__ __align__(1024) unsigned char smem[];
    const uint32_t sb = (uint32_t)__cvta_generic_to_shared(smem);
    const int tid = threadIdx.x, warp = tid >> 5, lane = tid & 31, cta = blockIdx.x;
    const uint32_t bars = sb + OFF_BAR;
    volatile int* ntot = reinterpret_cast<volatile int*>(smem + OFF_NTOT);
    const bool has_mod = cta >= MOD_C0, has_q = cta < NQ;
    const bool stat_wo = cta < C_X, extra = cta >= C_X && cta < C_P, pool_head = cta >= C_P && cta < C_E;

    const int t0 = static_begin(cta), t1 = static_begin(cta + 1);
    uint32_t xp = 0, cp = 0, epoch = 0;
    uint64_t pol = 0;
#define ISSUE_SLICE(i, map, off, bar, col)                                  \
    do {                                                                    \
        tma2d(sb + (off) + 8192 * (i), (map), (col), 128 * (i), (bar), pol); \
        if ((i) < 4) tma2d(sb + (off) + 8192 * (i) + 4096, (map), (col), 128 * (i) + 64, (bar), pol); \
    } while (0)
    if (tid == 32 * W_RED) {
        asm volatile("cp.async.bulk.prefetch.L2.global [%0], %1;" ::"l"(ptr.k + (size_t)t0 * (ITEM / 2)), "n"(ITEM) : "memory");
#pragma unroll
        for (int b = 0; b < 27; b++) mbar_init(bars + 8 * b, 1);
        asm volatile("fence.proxy.async.shared::cta;" ::: "memory");
    } else if (tid == 32 * W_PROD) {
        const CUtensorMap* m0 = has_mod ? &maps.wmod : &maps.wq;
        prefetch_map(m0);
        prefetch_map(&maps.wq);
        prefetch_map(&maps.k);
        prefetch_map(&maps.v);
#pragma unroll
        for (int b = B_WMOD; b < B_END; b++) mbar_init(bars + 8 * b, 1);
        asm volatile("fence.proxy.async.shared::cta;" ::: "memory");
        asm volatile("createpolicy.fractional.L2::evict_first.b64 %0, 1.0;" : "=l"(pol));
        const uint32_t b0 = bars + 8 * (has_mod ? B_WMOD : B_WQ), off = has_mod ? OFF_WMOD : OFF_WQ;
        const int col = 32 * (has_mod ? cta - MOD_C0 : cta);
#pragma unroll
        for (int i = 0; i < 5; i++) {
            mbar_expect(b0 + 8 * i, i < 4 ? 8192 : 4096);
            ISSUE_SLICE(i, m0, off, b0 + 8 * i, col);
        }
    } else if (tid == 32 * W_RED + 32) {
#pragma unroll
        for (int b = 27; b < B_WMOD; b++) mbar_init(bars + 8 * b, 1);
        asm volatile("fence.proxy.async.shared::cta;" ::: "memory");
        ntot[0] = 0x7fffffff;
        ntot[1] = 0;
    } else if (warp < NCW) {
        TL0(0);
        asm volatile("ld.global.nc.u32 %0, [%1];" : "=r"(cp) : "l"(ptr.c + 2 * tid));
        asm volatile("ld.global.nc.u32 %0, [%1];" : "=r"(xp) : "l"(ptr.x + 2 * tid));
        if (warp == 0) {
            if (has_mod) stg1(g_mod + 32 * (cta - MOD_C0) + lane, 0);
            if (has_q) stg1(g_q + 32 * cta + lane, 0);
        }
    }
    __syncwarp();
    if (warp != W_PROD) asm volatile("ld.relaxed.gpu.global.u32 %0, [%1];" : "=r"(epoch) : "l"(&g_epoch) : "memory");
    __syncthreads();

    const int head0 = t0 / TPH;
    const int n0 = min(t1, (head0 + 1) * TPH) - t0;
    const int n01 = t1 - t0;
    const int woff = (-n01) & (NAS - 1);
    const int cnt_pool = 32 * (NCW + (cta < NRED ? 2 : 0));

    if (warp == W_PROD) {
        if (lane == 0) {
            if (sb & 1023) __trap();
            const uint32_t c_start = clk();
            uint32_t hist[DMAX];
#pragma unroll
            for (int i = 0; i < DMAX; i++) hist[i] = i < 5 ? bars + 8 * ((has_mod ? B_WMOD : B_WQ) + 4 - i) : (bars + 8 * B_EMPTY) | 1u;
#define PUSH_ITEM(bar, par)                                                 \
            do {                                                            \
                _Pragma("unroll") for (int i_ = DMAX - 1; i_ > 0; i_--) hist[i_] = hist[i_ - 1]; \
                hist[0] = (bar) | (par);                                    \
            } while (0)
            uint32_t phm = 0;
#define ISSUE_TILE(D, t, w, paced)                                          \
            do {                                                            \
                const uint32_t ph_ = (phm >> (w)) & 1u;                     \
                const uint32_t fb_ = bars + 16 * (w), dst_ = sb + OFF_SLOT0 + (((w) + NAS - NAP) & (NAS - 1)) * (2 * ITEM); \
                phm ^= 1u << (w);                                           \
                _Pragma("unroll") for (int kv_ = 0; kv_ < 2; kv_++) {       \
                    mbar_wait(fb_ + 8 * (B_EMPTY + kv_), ph_ ^ 1);          \
                    mbar_expect(fb_ + 8 * kv_, ITEM);                       \
                    if (paced) mbar_wait(hist[(D) - 1] & ~1u, hist[(D) - 1] & 1u); \
                    tma2d(dst_ + kv_ * ITEM, kv_ ? &maps.v : &maps.k, 0, (t) * (2 * TILE), fb_ + 8 * kv_, pol); \
                    PUSH_ITEM(fb_ + 8 * kv_, ph_);                          \
                }                                                           \
            } while (0)
#define PACE_TAIL(D)                                                        \
            do {                                                            \
                uint32_t n_ = 0;                                            \
                while (!ntot[1] && !mbar_test(hist[(D) - 1] & ~1u, hist[(D) - 1] & 1u)) spin_guard(n_); \
            } while (0)

            if (has_mod && has_q) {
#pragma unroll 1
                for (int i = 0; i < 5; i++) {
                    const uint32_t bar = bars + 8 * (B_WQ + i);
                    mbar_expect(bar, i < 4 ? 8192 : 4096);
                    mbar_wait(hist[D_PRO - 1] & ~1u, hist[D_PRO - 1] & 1u);
                    ISSUE_SLICE(i, &maps.wq, OFF_WQ, bar, 32 * cta);
                    PUSH_ITEM(bar, 0u);
                }
            }
#pragma unroll 1
            for (int i = 0; i < NAS; i++) ISSUE_TILE(D_PRO, t0 + i, (i + woff) & (NAS - 1), true);
            TL(16);
#pragma unroll 1
            for (int i = NAS; i < n01; i++) {
                ISSUE_TILE(D_MAIN, t0 + i, (i + woff) & (NAS - 1), true);
            }
            TL(17);
            prefetch_map(&maps.wo); prefetch_map(&maps.gate); prefetch_map(&maps.up); prefetch_map(&maps.down);
            if (extra) { prefetch_map(&maps.gatex); prefetch_map(&maps.upx); }
            const int wo_row = pool_head ? 32 * cta : 40 * cta;
#define ISSUE_WO(D, i0, i1)                                                 \
            _Pragma("unroll 1") for (int i = (i0); i < (i1); i++) {         \
                const uint32_t bar = bars + 8 * (B_WO + i);                 \
                mbar_expect(bar, 9216);                                     \
                mbar_wait(hist[(D) - 1] & ~1u, hist[(D) - 1] & 1u);         \
                tma2d(sb + OFF_WO + 9216 * i, &maps.wo, 0, 9 * (wo_row + 8 * i), bar, pol); \
                PUSH_ITEM(bar, 0u);                                         \
            }
            ISSUE_WO(D_POOL, 0, pool_head ? 4 : stat_wo ? WO_EARLY : 0);
            uint32_t tk = atomicAdd(&g_ticket, 1u), c_tk = 0, left = 0;
            int n = 0, w = 0;
#pragma unroll 1
            while (tk < (uint32_t)NPOOL) {
                c_tk = clk();
                left = NPOOL - tk;
                ISSUE_TILE(D_POOL, NSTATIC + (int)tk, w, tk < (uint32_t)(NPOOL - BOOST));
                tk = atomicAdd(&g_ticket, 1u);
                n++;
                if (++w == NAP) w = 0;
            }
            ntot[0] = n;
            TL(18);
            uint32_t due = clk();
            const float cpm = (float)(due - c_start) * (T_SPEED / 540.0f);
            if (n) { const uint32_t dry = c_tk + (uint32_t)(cpm * (2 * ITEM * 1e-6f) * left); if ((int)(due - dry) > 0) due = dry; }
            due += (uint32_t)(cpm * T_LEAD);
#define PACE_TIME(step)                                                     \
            do {                                                            \
                uint32_t n_ = 0;                                            \
                mbar_wait(hist[D_CAP - 1] & ~1u, hist[D_CAP - 1] & 1u);     \
                while ((int)(clk() - due) < 0 && !(BURST && ntot[1])) spin_guard(n_); \
                due += (step);                                              \
            } while (0)
            uint32_t step = (uint32_t)(cpm * (T_WO * C_X * 9216e-6f));
            if (stat_wo) {
#pragma unroll 1
                for (int i = WO_EARLY; i < 5; i++) {
                    const uint32_t bar = bars + 8 * (B_WO + i);
                    mbar_expect(bar, 9216);
                    PACE_TIME(step);
                    tma2d(sb + OFF_WO + 9216 * i, &maps.wo, 0, 9 * (wo_row + 8 * i), bar, pol);
                    PUSH_ITEM(bar, 0u);
                }
            } else due += (5 - WO_EARLY) * step;
            step = (uint32_t)(cpm * (64 * FF * 4e-6f));
            TL(19);
            mbar_wait(bars + 8 * B_SDONE, 0);
            const int xcol = FX0 + 16 * (cta - C_X);
#pragma unroll 1
            for (int i = 0; i < 9; i++) {
                const uint32_t bar = bars + 8 * (B_GU + i);
                mbar_expect(bar, extra ? 12288 : 8192);
                PACE_TIME(step);
                tma2d(sb + OFF_GATE + 4096 * i, &maps.gate, 32 * cta, 64 * i, bar, pol);
                tma2d(sb + OFF_UP + 4096 * i, &maps.up, 32 * cta, 64 * i, bar, pol);
                if (extra) {
                    tma2d(sb + OFF_GATEX + 2048 * i, &maps.gatex, xcol, 64 * i, bar, pol);
                    tma2d(sb + OFF_UPX + 2048 * i, &maps.upx, xcol, 64 * i, bar, pol);
                }
                PUSH_ITEM(bar, 0u);
            }
            TL(20);
            mbar_wait(bars + 8 * B_PDONE, 0);
            step = (uint32_t)(cpm * (extra ? T_DOWN * FF * 1152e-6f / 4 * 0.6f : T_DOWN * FF * 1152e-6f / 4));
#pragma unroll 1
            for (int i = 0; i < (extra ? 6 : 4); i++) {
                const uint32_t bar = bars + 8 * (B_DOWN + i);
                mbar_expect(bar, 9216);
                PACE_TIME(step);
                tma2d(sb + OFF_DOWN + 9216 * i, &maps.down, 0, 9 * (i < 4 ? 32 * cta + 8 * i : xcol + 8 * (i - 4)), bar, pol);
                PUSH_ITEM(bar, 0u);
            }
            TL(21);
        }
        return;
    }

    const uint32_t tag = epoch >= 3u ? 1u : epoch + 1u;

    if (warp >= W_RED) {
        const int half = warp - W_RED, col = 8 * cta + 4 * (lane & 1);
        const bool wr = !half && lane < 2;
        uint32_t* vec = reinterpret_cast<uint32_t*>(smem + OFF_VEC);
        float4* xch = reinterpret_cast<float4*>(vec + 48);
        uint4 gb;
        uint32_t x0, x1;
        float s[4];
        if (cta < NRED) {
            bar_sync(3, cnt_pool);
            uint32_t* const xs = g_x1 + (lane >> 2) * DM + col + (lane & 2);
            const bool wx = !half && lane < 4 * XREP;
            if (wx) stg2(xs, 0, 0);
            const uint2 xq = *reinterpret_cast<const uint2*>(ptr.x + col);
            uint4 ga;
            uint32_t n = 0;
            do { ga = ldg4(g_mod + 2 * DM + col); gb = ldg4(g_mod + 5 * DM + col); spin_guard(n); } while (bad4(ga, tag) | bad4(gb, tag));
            mbar_wait(bars + 8 * (B_GU + Y_GATE), 0);
            reduce_cols<NY>(g_y + cta * (NY * 8), half, lane, tag, xch, s);
            uint32_t p0 = pack2(s[0], s[1]), p1 = pack2(s[2], s[3]);
            p0 = pack2(untag(ga.x) * blo(p0), untag(ga.y) * bhi(p0));
            p1 = pack2(untag(ga.z) * blo(p1), untag(ga.w) * bhi(p1));
            x0 = pack2(blo(xq.x) + blo(p0), bhi(xq.x) + bhi(p0));
            x1 = pack2(blo(xq.y) + blo(p1), bhi(xq.y) + bhi(p1));
            const uint32_t xw = (lane & 2) ? x1 : x0;
            if (wx) red2(xs, (xw << 16) | tag, (xw & 0xffff0000u) | tag);
            if (tid == 32 * W_RED) TL(24);
        }
        {
            const int pr = 12 * half + min(lane & 15, 11);
            const float* q = reinterpret_cast<const float*>(smem + OFF_RED) + 720 + 2 * pr + 48 * (lane >> 4);
            bar_sync(4, 32 * (NCW + 2));
            float2 v[NCW];
#pragma unroll
            for (int w = 0; w < NCW; w++) v[w] = *reinterpret_cast<const float2*>(q + 96 * w);
#define SUM9(f) ((((v[0].f + v[1].f) + (v[2].f + v[3].f)) + ((v[4].f + v[5].f) + (v[6].f + v[7].f))) + v[8].f)
            const uint32_t a = pack2(SUM9(x), SUM9(y)), b = __shfl_xor_sync(0xffffffffu, a, 16);
#undef SUM9
            if (lane < 12) vec[24 + pr] = pack2(blo(a) * blo(b), bhi(a) * bhi(b));
            asm volatile("bar.arrive 8, %0;" ::"n"(32 * (NCW + 2)) : "memory");
        }
        if (cta < NRED) {
            bar_sync(6, 32 * (NCW + 2));
            reduce_cols<NCTA>(g_z + cta * (NCTA * 8), half, lane, tag, xch + 2, s);
            uint32_t p0 = pack2(s[0], s[1]), p1 = pack2(s[2], s[3]);
            p0 = pack2(untag(gb.x) * blo(p0), untag(gb.y) * bhi(p0));
            p1 = pack2(untag(gb.z) * blo(p1), untag(gb.w) * bhi(p1));
            if (wr)
                *reinterpret_cast<uint2*>(ptr.out + col) =
                    make_uint2(pack2(blo(x0) + blo(p0), bhi(x0) + bhi(p0)), pack2(blo(x1) + blo(p1), bhi(x1) + bhi(p1)));
            if (cta == 0 && tid == 32 * W_RED) { g_ticket = 0; g_epoch = tag; }
            if (tid == 32 * W_RED) TL(25);
        }
        return;
    }

    float* red = reinterpret_cast<float*>(smem + OFF_RED);
    float* stat = reinterpret_cast<float*>(smem + OFF_STAT);
    const int g = lane >> 2, tig = lane & 3;
    uint32_t cb1 = 0, sbp = 0;
    {
        const float xa = blo(xp), xb = bhi(xp);
        ln_stats_part(xa, xb, stat, warp, lane);
        if (has_mod) {
            const float ca = blo(cp), cb = bhi(cp);
            cp = pack2(ca * rcp(1.0f + ex2(-1.4426950408889634f * ca)), cb * rcp(1.0f + ex2(-1.4426950408889634f * cb)));
            mbar_wait(bars + 8 * (B_WMOD + (warp >> 1)), 0);
            gemv32(sb + OFF_WMOD + 4096 * warp, cp, red + 80 * warp, lane);
        }
        bar_sync(2, 32 * NCW);
        if (has_mod && warp == 0) red1(g_mod + 32 * (cta - MOD_C0) + lane, __float_as_uint(rbf(sum9(red + lane))) | tag);
        TL0(1);
        if (has_q) {
            float mean, rsd;
            ln_stats_fin(stat, mean, rsd);
            mbar_wait(bars + 8 * (B_WQ + (warp >> 1)), 0);
            uint2 sa, ca;
            uint32_t n = 0;
            do { sa = ldg2(g_mod + 2 * tid); ca = ldg2(g_mod + DM + 2 * tid); spin_guard(n); } while (bad2(sa, tag) | bad2(ca, tag));
            TL0(2);
            const uint32_t hp = ln_apply(xa, xb, mean, rsd, pack2(1.0f + untag(ca.x), 1.0f + untag(ca.y)), __byte_perm(sa.x, sa.y, 0x7632));
            __syncwarp();
            gemv32(sb + OFF_WQ + 4096 * warp, hp, red + 720 + 80 * warp, lane);
            bar_sync(2, 32 * NCW);
            if (warp == 0) red1(g_q + 32 * cta + lane, __float_as_uint(rbf(sum9(red + 720 + lane))) | tag);
            TL0(3);
        }
        {
            const int seg = tid >> 6;
            const int hd = seg == 0 ? head0 : seg == 1 ? head0 + 1 : HKV - 1;
            uint4 v = make_uint4(tag, tag, tag, tag);
            uint2 s2 = make_uint2(0, 0), c2 = s2;
            uint32_t n = 0;
            do {
                if (tid < 192) v = ldg4(g_q + 256 * hd + 4 * (tid & 63));
                if (bad2(s2, tag) | bad2(c2, tag)) { s2 = ldg2(g_mod + 3 * DM + 2 * tid); c2 = ldg2(g_mod + 4 * DM + 2 * tid); }
                spin_guard(n);
            } while (bad4(v, tag) | bad2(s2, tag) | bad2(c2, tag));
            if (tid < 192)
                *reinterpret_cast<uint2*>(smem + OFF_Q + 8 * tid) = make_uint2(__byte_perm(v.x, v.y, 0x7632), __byte_perm(v.z, v.w, 0x7632));
            sbp = __byte_perm(s2.x, s2.y, 0x7632);
            cb1 = pack2(1.0f + untag(c2.x), 1.0f + untag(c2.y));
        }
        bar_sync(2, 32 * NCW);
        TL0(4);
    }
    uint32_t* const yslot = g_y + ((8 * warp + 2 * tig) * NY + (pool_head ? cta - (C_P - C_X) : cta)) * 8 + g;
    uint32_t* const zslot = g_z + ((8 * warp + 2 * tig) * NCTA + cta) * 8 + g;
#define ZERO_SLOTS()                                                        \
    do {                                                                    \
        if (stat_wo || pool_head) { stg1(yslot, 0); stg1(yslot + NY * 8, 0); } \
        stg1(zslot, 0); stg1(zslot + NCTA * 8, 0);                          \
    } while (0)

    if (warp < NAS) {
        const int r = lane & 7, var = r >> 2;
        const uint32_t kofs = (r + 8 * ((lane >> 3) & 1)) * 256, kx = (lane >> 4) ^ var ^ (2 * (r & 3));
        const uint32_t vofs = (r + 8 * (lane >> 4)) * 256, vx = ((lane >> 3) & 1) ^ var ^ (2 * (r & 3));
        const float bias = (tig == (g >> 2)) ? 0.f : -INFINITY;
        float* stage = reinterpret_cast<float*>(smem + OFF_STAGE);
        const uint32_t slot = sb + OFF_SLOT0 + ((warp + NAS - NAP) & (NAS - 1)) * (2 * ITEM);
        const uint32_t kb = slot + kofs, vb = slot + ITEM + vofs;
        const uint32_t kfull = bars + 16 * warp, kempty = kfull + 8 * B_EMPTY;
        int i = (warp - woff) & (NAS - 1);
        uint32_t ph = 0;
#pragma unroll 1
        for (int seg = 0; seg < 3; seg++) {
            if (seg == 1 && n01 == n0) continue;
            if (seg == 2) {
                ZERO_SLOTS();
                if (warp >= NAP) break;
                if (tid < 128) {
                    stg2(g_part + (cta * 3 + 2) * 256 + 2 * tid, 0, 0);
                    if ((tid & 63) < 2) stg2(g_ml + ((4 + (tid >> 6)) * 144 + cta) * 4 + 2 * (tid & 1), 0, 0);
                }
                i = warp;
            }
            uint32_t qf[8][2];
            {
                const uint32_t* qs = reinterpret_cast<const uint32_t*>(smem + OFF_Q) + 128 * seg + 64 * (g & 1) + tig;
                const int qv = (g >> 1) & 1;
#pragma unroll
                for (int s = 0; s < 8; s++) { qf[s][0] = qs[8 * s + 4 * qv]; qf[s][1] = qs[8 * s + 4 * (qv ^ 1)]; }
            }
            float o[8][4] = {};
            float m0 = NEG_BIG, m1 = NEG_BIG, l0 = 0.f, l1 = 0.f;
            const int end = seg == 0 ? n0 : n01;
            const int nw = seg == 2 ? NAP : NAS;
#pragma unroll 1
            for (;; i += nw) {
                if (seg < 2) {
                    if (i >= end) break;
                    mbar_wait(kfull, ph);
                } else {
                    bool stop = false;
                    uint32_t n = 0;
                    while (true) {
                        if (i >= ntot[0]) { stop = true; break; }
                        if (mbar_test(kfull, ph)) break;
                        spin_guard(n);
                    }
                    if (__any_sync(0xffffffffu, stop)) break;
                }
                float s[2][2][4] = {};
#pragma unroll
                for (int st = 0; st < 8; st++) {
#pragma unroll
                    for (int mt = 0; mt < 2; mt++) {
                        uint32_t a[4];
                        ldsm4(kb + mt * 4096 + (st >> 2) * 128 + (((2 * (st & 3)) ^ (st >> 2) ^ kx) << 4), a);
                        mma16816(s[mt][st & 1], a, qf[st][0], qf[st][1]);
                    }
                }
                __syncwarp();
                if (lane == 0) mbar_arrive(kempty);
                float t[2][4];
#pragma unroll
                for (int mt = 0; mt < 2; mt++)
#pragma unroll
                    for (int j = 0; j < 4; j += 2) {
                        uint32_t p = pack2(s[mt][0][j] + s[mt][1][j], s[mt][0][j + 1] + s[mt][1][j + 1]);
                        p = pack2(blo(p) * 0.08838834764831845f, bhi(p) * 0.08838834764831845f);
                        t[mt][j] = fmaf(blo(p), 1.4426950408889634f, bias);
                        t[mt][j + 1] = fmaf(bhi(p), 1.4426950408889634f, bias);
                    }
                float x0 = fmaxf(fmaxf(t[0][0], t[0][2]), fmaxf(t[1][0], t[1][2]));
                float x1 = fmaxf(fmaxf(t[0][1], t[0][3]), fmaxf(t[1][1], t[1][3]));
                if (__any_sync(0xffffffffu, x0 > m0 || x1 > m1)) {
#pragma unroll
                    for (int d = 16; d; d >>= 1) {
                        x0 = fmaxf(x0, __shfl_xor_sync(0xffffffffu, x0, d));
                        x1 = fmaxf(x1, __shfl_xor_sync(0xffffffffu, x1, d));
                    }
                    x0 = fmaxf(x0, m0); x1 = fmaxf(x1, m1);
                    const float a0 = ex2(m0 - x0), a1 = ex2(m1 - x1);
                    m0 = x0; m1 = x1;
                    l0 *= a0; l1 *= a1;
#pragma unroll
                    for (int j = 0; j < 8; j++) { o[j][0] *= a0; o[j][1] *= a1; o[j][2] *= a0; o[j][3] *= a1; }
                }
                uint32_t pb[2][2];
#pragma unroll
                for (int mt = 0; mt < 2; mt++) {
                    const float p0 = ex2(t[mt][0] - m0), p1 = ex2(t[mt][1] - m1), p2 = ex2(t[mt][2] - m0), p3 = ex2(t[mt][3] - m1);
                    l0 += p0 + p2; l1 += p1 + p3;
                    pb[mt][0] = movmat(pack2(p0, p1));
                    pb[mt][1] = movmat(pack2(p2, p3));
                }
                mbar_wait(kfull + 8, ph);
                if (seg == 2) TLM(28);
#pragma unroll
                for (int mt = 0; mt < 2; mt++) {
#pragma unroll
                    for (int j = 0; j < 8; j++) {
                        uint32_t a[4];
                        ldsm4t(vb + mt * 4096 + (j >> 2) * 128 + (((2 * (j & 3)) ^ (j >> 2) ^ vx) << 4), a);
                        mma16816(o[j], a, pb[mt][0], pb[mt][1]);
                    }
                }
                __syncwarp();
                if (lane == 0) mbar_arrive(kempty + 8);
                ph ^= 1;
            }
            if (seg == 2) TLM(5);
            l0 += __shfl_xor_sync(0xffffffffu, l0, 17); l1 += __shfl_xor_sync(0xffffffffu, l1, 17);
            float* sw = stage + 260 * warp;
#pragma unroll
            for (int j = 0; j < 8; j++) {
                const float u0 = o[j][0] + __shfl_xor_sync(0xffffffffu, o[j][2], 1);
                const float u1 = o[j][1] + __shfl_xor_sync(0xffffffffu, o[j][3], 1);
                if (tig < 2) { sw[16 * j + 8 * tig + g] = u0; sw[128 + 16 * j + 8 * tig + g] = u1; }
                if (j == 2 || j == 5) {
                    l0 += __shfl_xor_sync(0xffffffffu, l0, j == 2 ? 4 : 8);
                    l1 += __shfl_xor_sync(0xffffffffu, l1, j == 2 ? 4 : 8);
                }
            }
            if (lane == 0) *reinterpret_cast<float4*>(sw + 256) = make_float4(m0, l0, m1, l1);
            bar_sync(1, 32 * nw);
            if (tid == 128 && end == n01) mbar_arrive(bars + 8 * (seg == 2 ? B_PDONE : B_SDONE));
            if (tid < 128) {
                const int h = tid >> 6;
                float2 ml[NAS], ov[NAS];
                float M = NEG_BIG;
#pragma unroll
                for (int w = 0; w < NAS; w++) {
                    ml[w] = make_float2(NEG_BIG, 0.f); ov[w] = make_float2(0.f, 0.f);
                    if (w < NAP || seg < 2) {
                        ml[w] = *reinterpret_cast<const float2*>(stage + 260 * w + 256 + 2 * h);
                        ov[w] = *reinterpret_cast<const float2*>(stage + 260 * w + 2 * tid);
                    }
                    M = fmaxf(M, ml[w].x);
                }
                float a = 0.f, b = 0.f, L = 0.f;
#pragma unroll
                for (int w = 0; w < NAS; w++) {
                    const float e = ex2(ml[w].x - M);
                    a += e * ov[w].x; b += e * ov[w].y; L += e * ml[w].y;
                }
                uint32_t* po = g_part + (cta * 3 + seg) * 256 + 2 * tid;
                uint32_t* pm = g_ml + ((seg * 2 + h) * 144 + cta) * 4 + 2 * (tid & 1);
                const uint32_t w0 = tagw((tid & 1) ? L : M, tag), w1 = (__float_as_uint(M) << 2) | tag;
                if (seg == 2) {
                    red2(po, tagw(a, tag), tagw(b, tag));
                    if ((tid & 63) < 2) red2(pm, w0, w1);
                } else {
                    stg2(po, tagw(a, tag), tagw(b, tag));
                    if ((tid & 63) < 2) stg2(pm, w0, w1);
                }
            }
            if (seg < 2) { if (end == n01) bar_sync(3, cnt_pool); else bar_sync(1, 32 * NAS); }
        }
        TL0(6);
    } else {
        bar_sync(3, cnt_pool);
        ZERO_SLOTS();
    }

    uint32_t* vec = reinterpret_cast<uint32_t*>(smem + OFF_VEC);
    if (stat_wo) {
        const int u = tid - 32 * NAP;
        if (u >= 0 && u < 40) {
            const int row = 40 * cta + u, kvh = row >> 8, h = (row >> 7) & 1;
            int c_lo = (kvh * TPH * NCTA) / NSTATIC;
            while (static_begin(c_lo + 1) <= kvh * TPH) c_lo++;
            while (static_begin(c_lo) > kvh * TPH) c_lo--;
            const int seg0 = static_begin(c_lo) / TPH == kvh ? 0 : 1;
            uint4 ml[10];
            uint32_t ov[10], bad, spin = 0;
#pragma unroll
            for (int k = 0; k < 10; k++) {
                ov[k] = static_begin(c_lo + k) < (kvh + 1) * TPH ? 0 : tag;
                ml[k] = make_uint4(tagw(NEG_BIG, tag), ov[k], ov[k], ov[k]);
            }
            do {
#pragma unroll
                for (int k = 0; k < 10; k++) {
                    const int seg = k ? 0 : seg0;
                    if (bad4(ml[k], tag) | ((ov[k] ^ tag) & 3u)) {
                        ov[k] = ldg1(g_part + ((c_lo + k) * 3 + seg) * 256 + (row & 255));
                        ml[k] = ldg4(g_ml + ((seg * 2 + h) * 144 + c_lo + k) * 4);
                    }
                }
                bad = 0;
#pragma unroll
                for (int k = 0; k < 10; k++) bad |= bad4(ml[k], tag) | ((ov[k] ^ tag) & 3u);
                if (bad) __nanosleep(300);
                spin_guard(spin);
            } while (bad);
            float M = NEG_BIG, num = 0.f, den = 0.f;
#pragma unroll
            for (int k = 0; k < 10; k++) {
                ml[k].x = (ml[k].x & ~3u) | ((ml[k].y >> 2) & 3u);
                M = fmaxf(M, __uint_as_float(ml[k].x));
            }
#pragma unroll
            for (int k = 0; k < 10; k++) {
                const float e = ex2(__uint_as_float(ml[k].x) - M);
                num += e * untag(ov[k]);
                den += e * untag(ml[k].z);
            }
            reinterpret_cast<uint16_t*>(vec)[u] = (uint16_t)pack2(num * rcp(den), 0.f);
        }
        bar_sync(2, 32 * NCW);
        float c[4][4] = {};
#pragma unroll
        for (int s = 0; s < 3; s++) {
            const uint32_t b0 = vec[8 * s + tig], b1 = s < 2 ? vec[8 * s + 4 + tig] : 0u;
            uint32_t a[4][4];
            mbar_wait(bars + 8 * (B_WO + 2 * s), 0);
            if (s < 2) mbar_wait(bars + 8 * (B_WO + 2 * s + 1), 0);
            load_frags64(sb + OFF_WO, s, s == 2, warp, lane, a);
#pragma unroll
            for (int i = 0; i < 4; i++) mma16816(c[i], a[i], b0, b1);
        }
        float v0, v1;
        pick2(c, tig, v0, v1);
        red1(yslot, tagw(v0, tag));
        red1(yslot + NY * 8, tagw(v1, tag));
        TLM(7);
    } else if (pool_head) {
        uint32_t wa[2][4][4];
#pragma unroll
        for (int s = 0; s < 2; s++) {
            mbar_wait(bars + 8 * (B_WO + 2 * s), 0);
            mbar_wait(bars + 8 * (B_WO + 2 * s + 1), 0);
            load_frags64(sb + OFF_WO, s, false, warp, lane, wa[s]);
        }
        const int h = (cta >> 2) & 1, c0 = 16 * warp + (lane >> 3);
        if (warp >= NAP) mbar_wait(bars + 8 * B_PDONE, 0);
        const uint32_t* po = g_part + ((c0 * 3 + 2) * 2 + h) * 128 + 32 * (cta & 3) + 4 * (lane & 7);
        const uint32_t* pm = g_ml + ((4 + h) * 144 + c0) * 4;
        uint4 ov[4], ml[4];
#pragma unroll
        for (int k = 0; k < 4; k++) {
            const uint32_t w = c0 + 4 * k < NCTA ? 0 : tag;
            ov[k] = make_uint4(w, w, w, w);
            ml[k] = make_uint4(tagw(NEG_BIG, tag), w, w, w);
        }
        uint32_t bad, spin = 0;
        do {
#pragma unroll
            for (int k = 0; k < 4; k++) {
                if (bad4(ov[k], tag)) ov[k] = ldg4(po + k * (24 * 128));
                if (bad4(ml[k], tag)) ml[k] = ldg4(pm + k * 16);
            }
            bad = 0;
#pragma unroll
            for (int k = 0; k < 4; k++) bad |= bad4(ov[k], tag) | bad4(ml[k], tag);
            spin_guard(spin);
        } while (bad);
        __syncwarp();
        TLM(29);
        float mk[4];
#pragma unroll
        for (int k = 0; k < 4; k++) mk[k] = __uint_as_float((ml[k].x & ~3u) | ((ml[k].y >> 2) & 3u));
        float M = fmaxf(fmaxf(mk[0], mk[1]), fmaxf(mk[2], mk[3]));
        M = fmaxf(M, __shfl_xor_sync(0xffffffffu, M, 8));
        M = fmaxf(M, __shfl_xor_sync(0xffffffffu, M, 16));
        float a[5] = {};
#pragma unroll
        for (int k = 0; k < 4; k++) {
            const float e = ex2(mk[k] - M);
            a[0] += e * untag(ov[k].x); a[1] += e * untag(ov[k].y); a[2] += e * untag(ov[k].z); a[3] += e * untag(ov[k].w);
            a[4] += e * untag(ml[k].z);
        }
#pragma unroll
        for (int j = 0; j < 5; j++) a[j] += __shfl_xor_sync(0xffffffffu, a[j], 8);
#pragma unroll
        for (int j = 0; j < 5; j++) a[j] += __shfl_xor_sync(0xffffffffu, a[j], 16);
        if (lane < 8) *reinterpret_cast<float4*>(red + 40 * warp + 4 * lane) = make_float4(a[0], a[1], a[2], a[3]);
        if (lane == 0) *reinterpret_cast<float2*>(red + 40 * warp + 32) = make_float2(M, a[4]);
        if (warp < NCW - 1) {
            asm volatile("bar.arrive 7, %0;" ::"n"(32 * NCW) : "memory");
        } else {
            bar_sync(7, 32 * NCW);
            float2 sw[NCW];
            float ow[NCW], MM = NEG_BIG;
#pragma unroll
            for (int w = 0; w < NCW; w++) {
                sw[w] = *reinterpret_cast<const float2*>(red + 40 * w + 32);
                ow[w] = red[40 * w + lane];
                MM = fmaxf(MM, sw[w].x);
            }
            float num[2] = {}, den[2] = {};
#pragma unroll
            for (int w = 0; w < NCW; w++) { const float e = ex2(sw[w].x - MM); num[w & 1] += e * ow[w]; den[w & 1] += e * sw[w].y; }
            reinterpret_cast<uint16_t*>(vec)[lane] = (uint16_t)pack2((num[0] + num[1]) * rcp(den[0] + den[1]), 0.f);
            if (lane == 0) TL(13);
        }
        bar_sync(2, 32 * NCW);
        float c[4][4] = {};
#pragma unroll
        for (int s = 0; s < 2; s++) {
            const uint32_t b0 = vec[8 * s + tig], b1 = vec[8 * s + 4 + tig];
#pragma unroll
            for (int i = 0; i < 4; i++) mma16816(c[i], wa[s][i], b0, b1);
        }
        float v0, v1;
        pick2(c, tig, v0, v1);
        red1(yslot, tagw(v0, tag));
        red1(yslot + NY * 8, tagw(v1, tag));
        TLM(8);
    }

    {
        uint32_t ga[4][6][4];
        const int r = lane & 7, mhi = (lane >> 3) & 1, khi = lane >> 4;
        const uint32_t box = sb + (mhi ? OFF_UP : OFF_GATE) + 4096 * warp + (8 * khi + r) * 64;
        const uint32_t boxx = sb + (mhi ? OFF_UPX : OFF_GATEX) + 2048 * warp + (8 * khi + r) * 32;
#define LOAD_GU()                                                           \
        do {                                                                \
            _Pragma("unroll") for (int s = 0; s < 4; s++)                   \
                _Pragma("unroll") for (int i = 0; i < 4; i++) ldsm4t(box + s * 1024 + ((i ^ (r >> 1)) << 4), ga[s][i]); \
            if (extra) {                                                    \
                _Pragma("unroll") for (int s = 0; s < 4; s++)               \
                    _Pragma("unroll") for (int i = 0; i < 2; i++) ldsm4t(boxx + s * 512 + ((i ^ (r >> 2)) << 4), ga[s][4 + i]); \
            }                                                               \
        } while (0)
        const int gate = TIMED || stat_wo || extra ? X1_GATE : 8;
        mbar_wait(bars + 8 * (B_GU + min(warp, gate)), 0);
        bool have = false;
        uint2 xv = make_uint2(0, 0);
        uint32_t n = 0;
        while (true) {
            if (!have && __all_sync(0xffffffffu, mbar_test(bars + 8 * (B_GU + warp), 0))) {
                have = true;
                LOAD_GU();
            }
            if (n == 0) mbar_wait(bars + 8 * (B_GU + gate), 0);
            if (bad2(xv, tag)) xv = ldg2(g_x1 + (cta & (XREP - 1)) * DM + 2 * tid);
            if (!__any_sync(0xffffffffu, bad2(xv, tag))) break;
            spin_guard(n);
        }
        TLM(15);
        const float xa = untag(xv.x), xb = untag(xv.y);
        ln_stats_part(xa, xb, stat + 20, warp, lane);
        bar_sync(2, 32 * NCW);
        if (tid == 0) ntot[1] = 1;
        TL0(9);
        float mean, rsd;
        ln_stats_fin(stat + 20, mean, rsd);
        const uint32_t hp = ln_apply(xa, xb, mean, rsd, cb1, sbp);
        if (!have) {
            mbar_wait(bars + 8 * (B_GU + warp), 0);
            LOAD_GU();
        }
        if (tid == 256) TL(14);
        float c[6][4] = {};
        uint32_t b[4][2];
#pragma unroll
        for (int s = 0; s < 4; s++) {
            b[s][0] = __shfl_sync(0xffffffffu, hp, 8 * s + tig);
            b[s][1] = __shfl_sync(0xffffffffu, hp, 8 * s + 4 + tig);
#pragma unroll
            for (int i = 0; i < 4; i++) mma16816(c[i], ga[s][i], b[s][0], b[s][1]);
        }
        if (extra) {
#pragma unroll
            for (int s = 0; s < 4; s++)
#pragma unroll
                for (int i = 4; i < 6; i++) mma16816(c[i], ga[s][i], b[s][0], b[s][1]);
        }
        float* rw = red + 720 + 96 * warp + 48 * (tig & 1) + 8 * (tig >> 1) + g;
#pragma unroll
        for (int i = 0; i < 6; i += 2) {
            const float lo = (tig & 1) ? c[i][2] : c[i][0], hi = (tig & 1) ? c[i + 1][2] : c[i + 1][0];
            rw[8 * i] = (tig & 2) ? hi : lo;
        }
    }
    asm volatile("bar.arrive 4, %0;" ::"n"(32 * (NCW + 2)) : "memory");

    uint32_t da[3][4][4];
    const uint32_t ok = __ballot_sync(0xffffffffu, lane < 6 && mbar_test(bars + 8 * (B_DOWN + min(lane, 5)), 0));
    const int nd = (ok & 3u) != 3u ? 0 : (ok & 15u) != 15u ? 1 : ok != 63u ? 2 : 3;
    __syncwarp();
#pragma unroll
    for (int s = 0; s < 3; s++) if (s < nd) load_frags64(sb + OFF_DOWN, s, false, warp, lane, da[s]);
    bar_sync(8, 32 * (NCW + 2));
    TL0(10);
    {
        float c[4][4] = {};
#pragma unroll
        for (int s = 0; s < 3; s++) {
            if (s == 2 && !extra) break;
            const uint32_t b0 = vec[24 + 8 * s + tig], b1 = vec[24 + 8 * s + 4 + tig];
            if (s >= nd) {
                mbar_wait(bars + 8 * (B_DOWN + 2 * s), 0);
                mbar_wait(bars + 8 * (B_DOWN + 2 * s + 1), 0);
                load_frags64(sb + OFF_DOWN, s, false, warp, lane, da[s]);
            }
#pragma unroll
            for (int i = 0; i < 4; i++) mma16816(c[i], da[s][i], b0, b1);
        }
        float v0, v1;
        pick2(c, tig, v0, v1);
        red1(zslot, tagw(v0, tag));
        red1(zslot + NCTA * 8, tagw(v1, tag));
        if (cta < NRED) asm volatile("bar.arrive 6, %0;" ::"n"(32 * (NCW + 2)) : "memory");
    }
    TLM(11);
}

typedef CUresult (*EncodeFn)(CUtensorMap*, CUtensorMapDataType, cuuint32_t, void*, const cuuint64_t*, const cuuint64_t*,
                             const cuuint32_t*, const cuuint32_t*, CUtensorMapInterleave, CUtensorMapSwizzle,
                             CUtensorMapL2promotion, CUtensorMapFloatOOBfill);

void make_map(EncodeFn enc, CUtensorMap* m, void* p, uint64_t cols, uint64_t rows, uint32_t bc, uint32_t br, CUtensorMapSwizzle sw, int promo = 0) {
    cuuint64_t gd[2] = {cols, rows};
    cuuint64_t gs[1] = {cols * 2};
    cuuint32_t bd[2] = {bc, br};
    cuuint32_t es[2] = {1, 1};
    enc(m, CU_TENSOR_MAP_DATA_TYPE_BFLOAT16, 2, p, gd, gs, bd, es, CU_TENSOR_MAP_INTERLEAVE_NONE, sw,
        (CUtensorMapL2promotion)promo, CU_TENSOR_MAP_FLOAT_OOB_FILL_NONE);
}

}

extern "C" void kernel_launch(void* const* d_in, const int* in_sizes, int n_in, void* d_out, int out_size) {
    (void)in_sizes; (void)n_in; (void)out_size;
    EncodeFn enc = nullptr;
    cudaDriverEntryPointQueryResult qr;
    cudaGetDriverEntryPoint("cuTensorMapEncodeTiled", (void**)&enc, cudaEnableDefault, &qr);
    Maps maps;
    make_map(enc, &maps.k, d_in[1], 64, (uint64_t)HKV * SK * 2, 64, 2 * TILE, CU_TENSOR_MAP_SWIZZLE_128B);
    make_map(enc, &maps.v, d_in[2], 64, (uint64_t)HKV * SK * 2, 64, 2 * TILE, CU_TENSOR_MAP_SWIZZLE_128B);
    make_map(enc, &maps.wmod, d_in[10], 6 * DM, DM, 32, 64, CU_TENSOR_MAP_SWIZZLE_64B);
    make_map(enc, &maps.wq, d_in[3], 4096, DM, 32, 64, CU_TENSOR_MAP_SWIZZLE_64B);
    make_map(enc, &maps.wo, d_in[4], 64, 4096 * 9, 64, 72, CU_TENSOR_MAP_SWIZZLE_128B);
    make_map(enc, &maps.gate, d_in[6], FF, DM, 32, 64, CU_TENSOR_MAP_SWIZZLE_64B, GU_PROMO);
    make_map(enc, &maps.up, d_in[7], FF, DM, 32, 64, CU_TENSOR_MAP_SWIZZLE_64B, GU_PROMO);
    make_map(enc, &maps.gatex, d_in[6], FF, DM, 16, 64, CU_TENSOR_MAP_SWIZZLE_32B, GU_PROMO);
    make_map(enc, &maps.upx, d_in[7], FF, DM, 16, 64, CU_TENSOR_MAP_SWIZZLE_32B, GU_PROMO);
    make_map(enc, &maps.down, d_in[8], 64, FF * 9, 64, 72, CU_TENSOR_MAP_SWIZZLE_128B);
    cudaFuncSetAttribute(fused_kernel, cudaFuncAttributeMaxDynamicSharedMemorySize, SMEM_BYTES);
    typedef const __nv_bfloat16* P;
    const Ptrs ptr = {(P)d_in[1], (P)d_in[0], (P)d_in[9], (__nv_bfloat16*)d_out};
    fused_kernel<<<NCTA, NTHREADS, SMEM_BYTES, cudaStreamPerThread>>>(ptr, maps);
}
```

```cpp
#include <cuda_runtime.h>
#include <cuda_bf16.h>
#include <cuda.h>
#include <stdint.h>

namespace {

constexpr int DM = 576;
constexpr int SK = 65536;
constexpr int HKV = 16;
constexpr int FF = 4608;
constexpr int NCTA = 132;
constexpr int NQ = 128;
constexpr int MOD_C0 = 24;
constexpr int NRED = 72;
constexpr int C_X = 96, C_P = 120, C_E = 128;
constexpr int NY = C_X + (C_E - C_P);
constexpr int FX0 = 32 * NCTA;
static_assert(FX0 + 16 * (C_P - C_X) == FF && 40 * C_X == 256 * (HKV - 1), "weight split");

constexpr int TILE = 32;
constexpr int TPH = SK / TILE;
constexpr int NSTATIC = (HKV - 1) * TPH;
#define GRP 4
constexpr int NG = NCTA / GRP;
constexpr int NPOOL = TPH;
constexpr int ITEM = TILE * 256;

#define D_MAIN 6
#define D_POOL 5
#define D_TAIL 4
#define BOOST 0
#define D_WO D_TAIL
#define X1_GATE 6
#define Y_GATE 0
#define GU_PROMO 2
#define TIMED 1
#define T_LEAD 1.2f
#define T_SPEED 1.0f
#define T_DOWN 1.0f
#define T_WO 1.0f
#define JIT 5
#define E1_WAIT 0.f
#define PF_BYTES 4096
#define N_PRO 32
#define D_CAP 6
#define BURST 0
#define WO_EARLY 0
#define NPROBE 14
#define FORCE 0
#define D_DOWN D_TAIL
#define D_PRO 5
constexpr int DMAX = 8;

constexpr int NCW = 9;
constexpr int NAS = 8;
constexpr int NAP = 5;
constexpr int W_PROD = 9, W_RED = 10;
constexpr int NTHREADS = 12 * 32;

constexpr int OFF_WMOD = 0;
constexpr int OFF_WQ = 9 * 4096;
constexpr int OFF_WO = 0;
constexpr int OFF_GATEX = 0;
constexpr int OFF_UPX = 9 * 2048;
constexpr int OFF_GATE = 40 * 1152;
constexpr int OFF_UP = OFF_GATE + 9 * 4096;
constexpr int OFF_SLOT0 = 18 * 4096;
constexpr int OFF_RING = OFF_SLOT0 + 2 * (NAS - NAP) * ITEM;
constexpr int OFF_DOWN = OFF_RING;
constexpr int OFF_BAR = OFF_RING + 2 * NAP * ITEM;
constexpr int OFF_STAGE = OFF_BAR + 512;
constexpr int OFF_RED = OFF_STAGE + NAS * 260 * 4;
constexpr int OFF_Q = OFF_RED + 9 * (80 + 96) * 4;
constexpr int OFF_STAT = OFF_Q + 3 * 256 * 2;
constexpr int OFF_VEC = OFF_STAT + 2 * 20 * 4;
constexpr int OFF_SEL = OFF_VEC + 64 * 4;
constexpr int OFF_NTOT = OFF_SEL + 96 * 4;
constexpr int SMEM_BYTES = OFF_NTOT + 16;
static_assert(SMEM_BYTES <= 232448, "smem");
static_assert(OFF_UP + 9 * 4096 <= OFF_RING && OFF_GATE % 1024 == 0, "layout");

constexpr int B_EMPTY = 2 * NAS, B_WO = 4 * NAS, B_GU = B_WO + 5, B_DOWN = B_GU + 9, B_SDONE = B_DOWN + 3, B_PDONE = B_SDONE + 1,
              B_WMOD = B_PDONE + 1, B_WQ = B_WMOD + 5, B_END = B_WQ + 5;
static_assert(B_END <= 64, "barriers");

constexpr float NEG_BIG = -1.0e30f;
constexpr uint32_t SPIN_LIMIT = 1u << 22;

struct Maps { CUtensorMap wmod, wq, k, v, wo, gate, up, gatex, upx, down; };

__device__ uint32_t g_epoch;
__device__ uint32_t g_ticket;
__device__ __align__(128) uint32_t g_mod[6 * DM];
__device__ __align__(128) uint32_t g_q[4096];
__device__ __align__(128) uint32_t g_part[NCTA * 2 * 2 * 128];
__device__ __align__(128) uint32_t g_ml[2 * 2 * 144 * 4];
constexpr int BOX_P = 2 * NRED, BOX_X = BOX_P + 5 * 8, NBOX = BOX_X + 4;
constexpr int ZA = 20;
__device__ __align__(128) uint32_t g_boxes[(NBOX + 1) * 2048];
__device__ __align__(128) uint32_t g_sel[NRED + 8];

#define TLM(i)
#define TL(i)
#define TL0(i)

__device__ __forceinline__ void mbar_init(uint32_t b, uint32_t c) {
    asm volatile("mbarrier.init.shared::cta.b64 [%0], %1;" ::"r"(b), "r"(c) : "memory");
}
__device__ __forceinline__ void mbar_expect(uint32_t b, uint32_t bytes) {
    asm volatile("mbarrier.arrive.expect_tx.shared::cta.b64 _, [%0], %1;" ::"r"(b), "r"(bytes) : "memory");
}
__device__ __forceinline__ void mbar_arrive(uint32_t b) {
    asm volatile("mbarrier.arrive.shared::cta.b64 _, [%0];" ::"r"(b) : "memory");
}
__device__ __forceinline__ bool mbar_try(uint32_t b, uint32_t ph) {
    uint32_t ok;
    asm volatile("{\n.reg .pred p;\nmbarrier.try_wait.parity.shared::cta.b64 p, [%1], %2;\nselp.u32 %0, 1, 0, p;\n}"
                 : "=r"(ok) : "r"(b), "r"(ph) : "memory");
    return ok;
}
__device__ __forceinline__ bool mbar_test(uint32_t b, uint32_t ph) {
    uint32_t ok;
    asm volatile("{\n.reg .pred p;\nmbarrier.test_wait.parity.shared::cta.b64 p, [%1], %2;\nselp.u32 %0, 1, 0, p;\n}"
                 : "=r"(ok) : "r"(b), "r"(ph) : "memory");
    return ok;
}
__device__ __forceinline__ void mbar_wait(uint32_t b, uint32_t ph) {
    uint32_t n = 0;
    while (!mbar_try(b, ph)) { if (++n > SPIN_LIMIT) __trap(); }
}
__device__ __forceinline__ void tma2d(uint32_t dst, const CUtensorMap* m, int c0, int c1, uint32_t bar, uint64_t pol) {
    asm volatile("cp.async.bulk.tensor.2d.shared::cluster.global.mbarrier::complete_tx::bytes.L2::cache_hint "
                 "[%0], [%1, {%3, %4}], [%2], %5;"
                 ::"r"(dst), "l"(m), "r"(bar), "r"(c0), "r"(c1), "l"(pol) : "memory");
}
__device__ __forceinline__ void bar_sync(int id, int n) { asm volatile("bar.sync %0, %1;" ::"r"(id), "r"(n) : "memory"); }
__device__ __forceinline__ void ldsm4(uint32_t a, uint32_t (&r)[4]) {
    asm volatile("ldmatrix.sync.aligned.m8n8.x4.shared.b16 {%0,%1,%2,%3}, [%4];"
                 : "=r"(r[0]), "=r"(r[1]), "=r"(r[2]), "=r"(r[3]) : "r"(a) : "memory");
}
__device__ __forceinline__ void ldsm4t(uint32_t a, uint32_t (&r)[4]) {
    asm volatile("ldmatrix.sync.aligned.m8n8.x4.trans.shared.b16 {%0,%1,%2,%3}, [%4];"
                 : "=r"(r[0]), "=r"(r[1]), "=r"(r[2]), "=r"(r[3]) : "r"(a) : "memory");
}
__device__ __forceinline__ void mma16816(float (&c)[4], const uint32_t (&a)[4], uint32_t b0, uint32_t b1) {
    asm volatile("mma.sync.aligned.m16n8k16.row.col.f32.bf16.bf16.f32 {%0,%1,%2,%3}, {%4,%5,%6,%7}, {%8,%9}, {%0,%1,%2,%3};"
                 : "+f"(c[0]), "+f"(c[1]), "+f"(c[2]), "+f"(c[3])
                 : "r"(a[0]), "r"(a[1]), "r"(a[2]), "r"(a[3]), "r"(b0), "r"(b1));
}
__device__ __forceinline__ uint32_t movmat(uint32_t a) {
    uint32_t d; asm volatile("movmatrix.sync.aligned.m8n8.trans.b16 %0, %1;" : "=r"(d) : "r"(a)); return d;
}
__device__ __forceinline__ float ex2(float x) { float y; asm("ex2.approx.ftz.f32 %0, %1;" : "=f"(y) : "f"(x)); return y; }
__device__ __forceinline__ uint32_t pack2(float lo, float hi) {
    uint32_t r; asm("cvt.rn.bf16x2.f32 %0, %1, %2;" : "=r"(r) : "f"(hi), "f"(lo)); return r;
}
__device__ __forceinline__ float rbf(float x) { return __uint_as_float(pack2(0.f, x)); }
__device__ __forceinline__ float rcp(float x) { float y; asm("rcp.approx.ftz.f32 %0, %1;" : "=f"(y) : "f"(x)); return y; }
__device__ __forceinline__ float blo(uint32_t p) { return __uint_as_float(p << 16); }
__device__ __forceinline__ float bhi(uint32_t p) { return __uint_as_float(p & 0xffff0000u); }

__device__ __forceinline__ uint32_t tagw(float v, uint32_t tag) { return (__float_as_uint(v) & ~3u) | tag; }
__device__ __forceinline__ float untag(uint32_t w) { return __uint_as_float(w & ~3u); }
__device__ __forceinline__ void stg1(uint32_t* p, uint32_t a) {
    asm volatile("st.relaxed.gpu.global.u32 [%0], %1;" ::"l"(p), "r"(a) : "memory");
}
__device__ __forceinline__ void stg2(uint32_t* p, uint32_t a, uint32_t b) {
    asm volatile("st.relaxed.gpu.global.v2.u32 [%0], {%1,%2};" ::"l"(p), "r"(a), "r"(b) : "memory");
}
__device__ __forceinline__ void stg4(uint32_t* p, uint32_t a, uint32_t b, uint32_t c, uint32_t d) {
    asm volatile("st.relaxed.gpu.global.v4.u32 [%0], {%1,%2,%3,%4};" ::"l"(p), "r"(a), "r"(b), "r"(c), "r"(d) : "memory");
}
__device__ __forceinline__ void red1(uint32_t* p, uint32_t a) {
    asm volatile("red.relaxed.gpu.global.or.b32 [%0], %1;" ::"l"(p), "r"(a) : "memory");
}
__device__ __forceinline__ void red2(uint32_t* p, uint32_t a, uint32_t b) {
    asm volatile("{\n.reg .b64 t;\nmov.b64 t, {%1, %2};\nred.relaxed.gpu.global.or.b64 [%0], t;\n}" ::"l"(p), "r"(a), "r"(b) : "memory");
}
__device__ __forceinline__ uint32_t ldg1(const uint32_t* p) {
    uint32_t v; asm volatile("ld.relaxed.gpu.global.u32 %0, [%1];" : "=r"(v) : "l"(p) : "memory"); return v;
}
__device__ __forceinline__ uint2 ldg2(const uint32_t* p) {
    uint2 v; asm volatile("ld.relaxed.gpu.global.v2.u32 {%0,%1}, [%2];" : "=r"(v.x), "=r"(v.y) : "l"(p) : "memory"); return v;
}
__device__ __forceinline__ uint4 ldg4(const uint32_t* p) {
    uint4 v;
    asm volatile("ld.relaxed.gpu.global.v4.u32 {%0,%1,%2,%3}, [%4];" : "=r"(v.x), "=r"(v.y), "=r"(v.z), "=r"(v.w) : "l"(p) : "memory");
    return v;
}
__device__ __forceinline__ uint32_t bad2(uint2 v, uint32_t tag) { return ((v.x ^ tag) | (v.y ^ tag)) & 3u; }
__device__ __forceinline__ uint32_t bad4(uint4 v, uint32_t tag) {
    return ((v.x ^ tag) | (v.y ^ tag) | (v.z ^ tag) | (v.w ^ tag)) & 3u;
}
__device__ __forceinline__ uint32_t clk() { uint32_t c; asm volatile("mov.u32 %0, %%clock;" : "=r"(c)); return c; }
__device__ __forceinline__ void spin_guard(uint32_t& n) { if (++n > SPIN_LIMIT) __trap(); }

__device__ __forceinline__ void ln_stats_part(float a, float b, float* stat, int warp, int lane) {
    float s = a + b, q = a * a + b * b;
#pragma unroll
    for (int o = 16; o; o >>= 1) { s += __shfl_xor_sync(0xffffffffu, s, o); q += __shfl_xor_sync(0xffffffffu, q, o); }
    if (lane == 0) *reinterpret_cast<float2*>(stat + 2 * warp) = make_float2(s, q);
}
__device__ __forceinline__ void ln_stats_fin(const float* stat, float& mean, float& rsd) {
    const float4 a = *reinterpret_cast<const float4*>(stat), b = *reinterpret_cast<const float4*>(stat + 4),
                 c = *reinterpret_cast<const float4*>(stat + 8), d = *reinterpret_cast<const float4*>(stat + 12);
    const float2 e = *reinterpret_cast<const float2*>(stat + 16);
    const float mu = (((a.x + a.z) + (b.x + b.z)) + ((c.x + c.z) + (d.x + d.z)) + e.x) * (1.0f / DM);
    const float sq = (((a.y + a.w) + (b.y + b.w)) + ((c.y + c.w) + (d.y + d.w)) + e.y) * (1.0f / DM);
    mean = rbf(mu);
    const float v = rbf(rbf(fmaxf(fmaf(-mu, mu, sq), 0.f)) + 1e-5f);
    float sd;
    asm("sqrt.approx.ftz.f32 %0, %1;" : "=f"(sd) : "f"(v));
    rsd = rcp(rbf(sd));
}
__device__ __forceinline__ uint32_t ln_apply(float xa, float xb, float mean, float rsd, uint32_t scale1, uint32_t shift) {
    uint32_t p = pack2(xa - mean, xb - mean);
    p = pack2(blo(p) * rsd, bhi(p) * rsd);
    p = pack2(blo(p) * blo(scale1), bhi(p) * bhi(scale1));
    return pack2(blo(p) + blo(shift), bhi(p) + bhi(shift));
}

__device__ __forceinline__ void gemv32(uint32_t box, uint32_t vp, float* red, int lane) {
    const int r = lane & 7, mhi = (lane >> 3) & 1, khi = lane >> 4, tig = lane & 3, g = lane >> 2;
    float c[2][2][4] = {};
#pragma unroll
    for (int s = 0; s < 4; s++) {
        uint32_t b0 = __shfl_sync(0xffffffffu, vp, 8 * s + tig), b1 = __shfl_sync(0xffffffffu, vp, 8 * s + 4 + tig);
        const int row = 16 * s + 8 * khi + r;
#pragma unroll
        for (int i = 0; i < 2; i++) {
            uint32_t a[4];
            ldsm4t(box + row * 64 + (((2 * i + mhi) ^ (r >> 1)) << 4), a);
            mma16816(c[i][s & 1], a, b0, b1);
        }
    }
    const float v0 = (tig & 1) ? c[0][0][2] + c[0][1][2] : c[0][0][0] + c[0][1][0];
    const float v1 = (tig & 1) ? c[1][0][2] + c[1][1][2] : c[1][0][0] + c[1][1][0];
    red[8 * tig + g] = (tig & 2) ? v1 : v0;
}
__device__ __forceinline__ float sum9(const float* p) {
    return (((p[0] + p[80]) + (p[160] + p[240])) + ((p[320] + p[400]) + (p[480] + p[560]))) + p[640];
}

__device__ __forceinline__ void load_frags64(uint32_t base, int s, bool half, int w, int lane, uint32_t (&a)[4][4]) {
    const int r = lane & 7, mhi = (lane >> 3) & 1, khi = half ? 0 : lane >> 4;
    const int row = 16 * s + 8 * khi + r;
    const uint32_t line = base + (9 * row + w) * 128, x = mhi ^ ((row + w) & 7);
#pragma unroll
    for (int i = 0; i < 4; i++) ldsm4t(line + (((2 * i) ^ x) << 4), a[i]);
}
__device__ __forceinline__ void pick2(const float (&c)[4][4], int tig, float& v0, float& v1) {
    v0 = (tig & 2) ? ((tig & 1) ? c[3][0] : c[2][0]) : ((tig & 1) ? c[1][0] : c[0][0]);
    v1 = (tig & 2) ? ((tig & 1) ? c[3][2] : c[2][2]) : ((tig & 1) ? c[1][2] : c[0][2]);
}

__device__ __forceinline__ int col8(int lane) { return 4 * (lane & 1) + (lane & 2) + ((lane >> 2) & 1); }
__device__ __forceinline__ float warp_cols(float a, float b, float c, float d, int lane) {
    const bool p = lane & 2, q = lane & 4;
    const float k0 = (p ? c : a) + __shfl_xor_sync(0xffffffffu, p ? a : c, 2);
    const float k1 = (p ? d : b) + __shfl_xor_sync(0xffffffffu, p ? b : d, 2);
    float k = (q ? k1 : k0) + __shfl_xor_sync(0xffffffffu, q ? k0 : k1, 4);
    k += __shfl_xor_sync(0xffffffffu, k, 8);
    return k + __shfl_xor_sync(0xffffffffu, k, 16);
}

__device__ __forceinline__ uint32_t* mbox(int b, uint32_t side) {
    const uintptr_t base = (reinterpret_cast<uintptr_t>(g_boxes) + 8191) & ~(uintptr_t)8191;
    return reinterpret_cast<uint32_t*>(base) + (2 * b + (side & 1u)) * 1024;
}
__device__ __forceinline__ int group_begin(int q) { return (NSTATIC * q) / NG; }
__device__ __forceinline__ void prefetch_map(const CUtensorMap* m) { asm volatile("prefetch.tensormap [%0];" ::"l"(m) : "memory"); }

struct Ptrs { const __nv_bfloat16 *k, *x, *c; __nv_bfloat16* out; };

__global__ void __launch_bounds__(NTHREADS, 1)
fused_kernel(const __grid_constant__ Ptrs ptr, const __grid_constant__ Maps maps) {
    extern __shared__ __align__(1024) unsigned char smem[];
    const uint32_t sb = (uint32_t)__cvta_generic_to_shared(smem);
    const int tid = threadIdx.x, warp = tid >> 5, lane = tid & 31, cta = blockIdx.x;
    const uint32_t bars = sb + OFF_BAR;
    volatile int* ntot = reinterpret_cast<volatile int*>(smem + OFF_NTOT);
    const bool has_mod = cta >= MOD_C0, has_q = cta < NQ;
    const bool stat_wo = cta < C_X, extra = cta >= C_X && cta < C_P, pool_head = cta >= C_P && cta < C_E;

    const int g0 = group_begin(cta / GRP), t0 = g0 + cta % GRP, t1 = group_begin(cta / GRP + 1);
    uint32_t xp = 0, cp = 0, epoch = 0;
    uint64_t pol = 0;
#define ISSUE_SLICE(i, map, off, bar, col)                                  \
    do {                                                                    \
        tma2d(sb + (off) + 8192 * (i), (map), (col), 128 * (i), (bar), pol); \
        if ((i) < 4) tma2d(sb + (off) + 8192 * (i) + 4096, (map), (col), 128 * (i) + 64, (bar), pol); \
    } while (0)
    if (tid == 0) {
        asm volatile("cp.async.bulk.prefetch.L2.global [%0], %1;" ::"l"(ptr.k + (size_t)t0 * (ITEM / 2)), "n"(PF_BYTES) : "memory");
        const CUtensorMap* m0 = has_mod ? &maps.wmod : &maps.wq;
        prefetch_map(m0);
        const uint32_t b0 = bars + 8 * (has_mod ? B_WMOD : B_WQ), off = has_mod ? OFF_WMOD : OFF_WQ;
        const int col = 32 * (has_mod ? cta - MOD_C0 : cta);
#pragma unroll
        for (int i = 0; i < 5; i++) mbar_init(b0 + 8 * i, 1);
        asm volatile("fence.proxy.async.shared::cta;" ::: "memory");
        asm volatile("createpolicy.fractional.L2::evict_first.b64 %0, 1.0;" : "=l"(pol));
#pragma unroll
        for (int i = 0; i < 5; i++) {
            mbar_expect(b0 + 8 * i, i < 4 ? 8192 : 4096);
            ISSUE_SLICE(i, m0, off, b0 + 8 * i, col);
        }
    }
    __syncwarp();
    if (tid == 32 * W_RED) {
#pragma unroll
        for (int b = 0; b < 27; b++) mbar_init(bars + 8 * b, 1);
        asm volatile("fence.proxy.async.shared::cta;" ::: "memory");
    } else if (tid == 32 * W_PROD) {
        prefetch_map(&maps.wq);
        prefetch_map(&maps.k);
        prefetch_map(&maps.v);
        if (has_mod) {
#pragma unroll
            for (int b = B_WQ; b < B_END; b++) mbar_init(bars + 8 * b, 1);
        }
        asm volatile("fence.proxy.async.shared::cta;" ::: "memory");
        asm volatile("createpolicy.fractional.L2::evict_first.b64 %0, 1.0;" : "=l"(pol));
    } else if (tid == 32 * W_RED + 32) {
#pragma unroll
        for (int b = 27; b < B_WMOD; b++) mbar_init(bars + 8 * b, b >= B_DOWN && b < B_SDONE ? 2 : 1);
        asm volatile("fence.proxy.async.shared::cta;" ::: "memory");
        ntot[0] = 0x7fffffff;
        ntot[1] = 0;
    } else if (warp < NCW) {
        if (tid == 32) TL(0);
        asm volatile("ld.global.nc.u32 %0, [%1];" : "=r"(cp) : "l"(ptr.c + 2 * tid));
        asm volatile("ld.global.nc.u32 %0, [%1];" : "=r"(xp) : "l"(ptr.x + 2 * tid));
        if (warp == 0) {
            if (has_mod) stg1(g_mod + 32 * (cta - MOD_C0) + lane, 0);
            if (has_q) stg1(g_q + 32 * cta + lane, 0);
        }
    }
    __syncwarp();
    if (warp != W_PROD) asm volatile("ld.relaxed.gpu.global.u32 %0, [%1];" : "=r"(epoch) : "l"(&g_epoch) : "memory");
    __syncthreads();

    const int head0 = g0 / TPH;
    const int last_seg = t1 > (head0 + 1) * TPH;
    const int n0 = (min(t1, (head0 + 1) * TPH) - t0 + GRP - 1) / GRP;
    const int n01 = (t1 - t0 + GRP - 1) / GRP;
    const int woff = (-n01) & (NAS - 1);

    if (warp == W_PROD) {
        if (lane == 0) {
            if (sb & 1023) __trap();
            const uint32_t c_start = clk();
            uint32_t hist[DMAX];
#pragma unroll
            for (int i = 0; i < DMAX; i++) hist[i] = i < 5 ? bars + 8 * ((has_mod ? B_WMOD : B_WQ) + 4 - i) : (bars + 8 * B_EMPTY) | 1u;
#define PUSH_ITEM(bar, par)                                                 \
            do {                                                            \
                _Pragma("unroll") for (int i_ = DMAX - 1; i_ > 0; i_--) hist[i_] = hist[i_ - 1]; \
                hist[0] = (bar) | (par);                                    \
            } while (0)
            uint32_t phm = 0;
#define ISSUE_TILE(D, t, w, paced)                                          \
            do {                                                            \
                const uint32_t ph_ = (phm >> (w)) & 1u;                     \
                const uint32_t fb_ = bars + 16 * (w), dst_ = sb + OFF_SLOT0 + (((w) + NAS - NAP) & (NAS - 1)) * (2 * ITEM); \
                phm ^= 1u << (w);                                           \
                _Pragma("unroll") for (int kv_ = 0; kv_ < 2; kv_++) {       \
                    mbar_wait(fb_ + 8 * (B_EMPTY + kv_), ph_ ^ 1);          \
                    mbar_expect(fb_ + 8 * kv_, ITEM);                       \
                    if (paced) mbar_wait(hist[(D) - 1] & ~1u, hist[(D) - 1] & 1u); \
                    tma2d(dst_ + kv_ * ITEM, kv_ ? &maps.v : &maps.k, 0, (t) * (2 * TILE), fb_ + 8 * kv_, pol); \
                    PUSH_ITEM(fb_ + 8 * kv_, ph_);                          \
                }                                                           \
            } while (0)
#define PACE_TAIL(D)                                                        \
            do {                                                            \
                uint32_t n_ = 0;                                            \
                while (!ntot[1] && !mbar_test(hist[(D) - 1] & ~1u, hist[(D) - 1] & 1u)) spin_guard(n_); \
            } while (0)

            if (has_mod && has_q) {
#pragma unroll 1
                for (int i = 0; i < 5; i++) {
                    const uint32_t bar = bars + 8 * (B_WQ + i);
                    mbar_expect(bar, i < 4 ? 8192 : 4096);
                    mbar_wait(hist[D_PRO - 1] & ~1u, hist[D_PRO - 1] & 1u);
                    ISSUE_SLICE(i, &maps.wq, OFF_WQ, bar, 32 * cta);
                    PUSH_ITEM(bar, 0u);
                }
            }
#pragma unroll 1
            for (int i = 0; i < N_PRO; i++) ISSUE_TILE(D_PRO, t0 + GRP * i, (i + woff) & (NAS - 1), true);
            TL(16);
#pragma unroll 1
            for (int i = N_PRO; i < n01; i++) {
                ISSUE_TILE(D_MAIN, t0 + GRP * i, (i + woff) & (NAS - 1), true);
            }
            TL(17);
            prefetch_map(&maps.wo); prefetch_map(&maps.gate); prefetch_map(&maps.up); prefetch_map(&maps.down);
            if (extra) { prefetch_map(&maps.gatex); prefetch_map(&maps.upx); }
            const int wo_row = pool_head ? 32 * cta : 40 * cta;
#define ISSUE_WO(D, i0, i1)                                                 \
            _Pragma("unroll 1") for (int i = (i0); i < (i1); i++) {         \
                const uint32_t bar = bars + 8 * (B_WO + i);                 \
                mbar_expect(bar, 9216);                                     \
                mbar_wait(hist[(D) - 1] & ~1u, hist[(D) - 1] & 1u);         \
                tma2d(sb + OFF_WO + 9216 * i, &maps.wo, 0, 9 * (wo_row + 8 * i), bar, pol); \
                PUSH_ITEM(bar, 0u);                                         \
            }
            ISSUE_WO(D_POOL, 0, pool_head ? 4 : stat_wo ? WO_EARLY : 0);
            uint32_t c_tk = 0, left = 0;
            int n = 0, w = 0;
#pragma unroll 1
            while (true) {
                const uint32_t ph = (phm >> w) & 1u, fb = bars + 16 * w, dst = sb + OFF_RING + w * (2 * ITEM);
                mbar_wait(hist[JIT - 1] & ~1u, hist[JIT - 1] & 1u);
                const uint32_t tk = atomicAdd(&g_ticket, 1u);
                mbar_wait(fb + 8 * (B_EMPTY + 1), ph ^ 1);
                if (tk >= (uint32_t)NPOOL) break;
                mbar_expect(fb, ITEM);
                tma2d(dst, &maps.k, 0, (NSTATIC + (int)tk) * (2 * TILE), fb, pol);
                mbar_expect(fb + 8, ITEM);
                tma2d(dst + ITEM, &maps.v, 0, (NSTATIC + (int)tk) * (2 * TILE), fb + 8, pol);
                c_tk = clk();
                left = NPOOL - tk;
                PUSH_ITEM(fb, ph);
                PUSH_ITEM(fb + 8, ph);
                phm ^= 1u << w;
                n++;
                if (++w == NAP) w = 0;
            }
            uint32_t due = clk();
            const float cpm = (float)(due - c_start) * (T_SPEED / 540.0f);
            if (n) { const uint32_t dry = c_tk + (uint32_t)(cpm * (2 * ITEM * 1e-6f) * left); if ((int)(due - dry) > 0) due = dry; }
            ntot[2] = (int)(due + (uint32_t)(cpm * E1_WAIT));
            ntot[0] = n;
            TL(18);
            due += (uint32_t)(cpm * T_LEAD);
#define PACE_TIME(step)                                                     \
            do {                                                            \
                uint32_t n_ = 0;                                            \
                mbar_wait(hist[D_CAP - 1] & ~1u, hist[D_CAP - 1] & 1u);     \
                while ((int)(clk() - due) < 0 && !(BURST && ntot[1])) spin_guard(n_); \
                due += (step);                                              \
            } while (0)
            uint32_t step = (uint32_t)(cpm * (T_WO * C_X * 9216e-6f));
            if (stat_wo) {
#pragma unroll 1
                for (int i = WO_EARLY; i < 5; i++) {
                    const uint32_t bar = bars + 8 * (B_WO + i);
                    mbar_expect(bar, 9216);
                    PACE_TIME(step);
                    tma2d(sb + OFF_WO + 9216 * i, &maps.wo, 0, 9 * (wo_row + 8 * i), bar, pol);
                    PUSH_ITEM(bar, 0u);
                }
            } else due += (5 - WO_EARLY) * step;
            step = (uint32_t)(cpm * (64 * FF * 4e-6f));
            TL(19);
            mbar_wait(bars + 8 * B_SDONE, 0);
            const int xcol = FX0 + 16 * (cta - C_X);
#pragma unroll 1
            for (int i = 0; i < 9; i++) {
                const uint32_t bar = bars + 8 * (B_GU + i);
                mbar_expect(bar, extra ? 12288 : 8192);
                PACE_TIME(step);
                tma2d(sb + OFF_GATE + 4096 * i, &maps.gate, 32 * cta, 64 * i, bar, pol);
                tma2d(sb + OFF_UP + 4096 * i, &maps.up, 32 * cta, 64 * i, bar, pol);
                if (extra) {
                    tma2d(sb + OFF_GATEX + 2048 * i, &maps.gatex, xcol, 64 * i, bar, pol);
                    tma2d(sb + OFF_UPX + 2048 * i, &maps.upx, xcol, 64 * i, bar, pol);
                }
                PUSH_ITEM(bar, 0u);
            }
            TL(20);
            mbar_wait(bars + 8 * B_PDONE, 0);
            step = (uint32_t)(cpm * (extra ? T_DOWN * FF * 1152e-6f / 4 * 0.6f : T_DOWN * FF * 1152e-6f / 4));
#pragma unroll 1
            for (int i = 0; i < (extra ? 6 : 4); i++) {
                const uint32_t bar = bars + 8 * (B_DOWN + (i >> 1));
                mbar_expect(bar, 9216);
                PACE_TIME(step);
                tma2d(sb + OFF_DOWN + 9216 * i, &maps.down, 0, 9 * (i < 4 ? 32 * cta + 8 * i : xcol + 8 * (i - 4)), bar, pol);
                PUSH_ITEM(bar, 0u);
            }
            TL(21);
        }
        return;
    }

    const uint32_t tag = epoch >= 3u ? 1u : epoch + 1u;

    if (warp >= W_RED) {
        const int half = warp - W_RED, col = 8 * cta + col8(lane);
        uint32_t* vec = reinterpret_cast<uint32_t*>(smem + OFF_VEC);
        uint32_t* sel = reinterpret_cast<uint32_t*>(smem + OFF_SEL);
        {
            const int nb = cta < NRED ? 2 : pool_head ? 5 : 0, b0 = cta < NRED ? 2 * cta : BOX_P + 5 * (cta - C_P);
            mbar_wait(bars + 8 * (B_EMPTY + 1), 0);
            uint32_t* const pw = mbox(lane < nb ? b0 + lane : BOX_X + (cta & 3), half) + DM + 8 * ((cta >> 2) & 7);
            if (lane <= nb) {
#pragma unroll 1
                for (int j = 0; j < 7; j++) { stg4(pw + 64 * j, 0, 0, 0, 0); stg4(pw + 64 * j + 4, 0, 0, 0, 0); }
            }
            uint32_t best = ~0u;
#pragma unroll 1
            for (int r = 0; r < NPROBE * (nb + 1); r++) {
                if (lane == r % (nb + 1)) {
                    uint32_t* const q = pw + 64 * (r % 7);
                    const uint32_t c0 = clk();
                    uint32_t v, c1;
                    asm volatile("atom.relaxed.gpu.global.add.u32 %0, [%1], 4;" : "=r"(v) : "l"(q) : "memory");
                    asm volatile("{\n.reg .pred p;\nsetp.eq.u32 p, %1, 0xffffffff;\n@p trap;\nmov.u32 %0, %%clock;\n}" : "=r"(c1) : "r"(v) : "memory");
                    best = min(best, c1 - c0);
                }
                __syncwarp();
            }
            if (lane < 8) sel[80 + 8 * half + lane] = best;
            bar_sync(5, 64);
            uint32_t sides = __ballot_sync(0xffffffffu, lane <= nb && sel[88 + (lane & 7)] < sel[80 + (lane & 7)]);
            if (FORCE == 1) sides = 0;
            if (FORCE == 2) sides = ~sides & 63u;
            bar_sync(5, 64);
            for (int b = 0; b < nb; b++) {
                uint32_t* q = mbox(b0 + b, sides >> b) + 4 * (32 * half + lane);
#pragma unroll
                for (int i = 0; i < 4; i++) stg4(q + 256 * i, 0, 0, 0, 0);
            }
            __threadfence();
            bar_sync(5, 64);
            if (!half && lane == 0) {
                if (nb) stg1(g_sel + (cta < NRED ? cta : NRED + cta - C_P), (sides << 2) | tag);
                sel[80] = sides >> nb;
            }
            for (int i = 32 * half + lane; i < NRED + 8; i += 64) {
                uint32_t v, n = 0;
                do { __nanosleep(4000); v = ldg1(g_sel + i); spin_guard(n); } while ((v ^ tag) & 3u);
                sel[i] = v >> 2;
            }
            __threadfence();
        }
        bar_sync(3, 32 * (NCW + 2));
        float x1 = 0.f, gb = 0.f;
        if (cta < NRED) {
            uint32_t* const xs = mbox(BOX_X + (lane >> 3), 0) + col;
            if (!half) { stg1(xs, 0); stg1(xs + 1024, 0); }
            const float x0 = __bfloat162float(ptr.x[col]);
            uint2 gm;
            uint32_t n = 0, bad;
            do { gm.x = ldg1(g_mod + 2 * DM + col); gm.y = ldg1(g_mod + 5 * DM + col); spin_guard(n); } while (bad2(gm, tag));
            gb = untag(gm.y);
            const int t = 32 * half + lane;
            const uint32_t* src = mbox(2 * cta, sel[cta]) + 4 * t;
            uint4 v[4];
#pragma unroll
            for (int i = 0; i < 4; i++) {
                const uint32_t w = 64 * i + t < 2 * NY ? 0 : tag;
                v[i] = make_uint4(w, w, w, w);
            }
            mbar_wait(bars + 8 * (B_GU + Y_GATE), 0);
            do {
#pragma unroll
                for (int i = 0; i < 4; i++) if (bad4(v[i], tag)) v[i] = ldg4(src + 256 * i);
                bad = bad4(v[0], tag) | bad4(v[1], tag) | bad4(v[2], tag) | bad4(v[3], tag);
                spin_guard(n);
            } while (bad);
            __syncwarp();
            TLM(30);
#define SUM4(f) ((untag(v[0].f) + untag(v[1].f)) + (untag(v[2].f) + untag(v[3].f)))
            const float k = warp_cols(SUM4(x), SUM4(y), SUM4(z), SUM4(w), lane);
#undef SUM4
            if (half) {
                if (lane < 8) vec[48 + lane] = __float_as_uint(k);
                asm volatile("bar.arrive 5, 64;" ::: "memory");
            } else {
                bar_sync(5, 64);
                x1 = rbf(x0 + rbf(untag(gm.x) * rbf(k + __uint_as_float(vec[48 + (lane & 7)]))));
                stg1(xs, __float_as_uint(x1) | tag);
                stg1(xs + 1024, __float_as_uint(x1) | tag);
                if (lane == 0) TL(24);
            }
        }
        {
            const int pr = 12 * half + min(lane & 15, 11);
            const float* q = reinterpret_cast<const float*>(smem + OFF_RED) + 720 + 2 * pr + 48 * (lane >> 4);
            bar_sync(4, 32 * (NCW + 2));
            float2 v[NCW];
#pragma unroll
            for (int w = 0; w < NCW; w++) v[w] = *reinterpret_cast<const float2*>(q + 96 * w);
#define SUM9(f) ((((v[0].f + v[1].f) + (v[2].f + v[3].f)) + ((v[4].f + v[5].f) + (v[6].f + v[7].f))) + v[8].f)
            const uint32_t a = pack2(SUM9(x), SUM9(y)), b = __shfl_xor_sync(0xffffffffu, a, 16);
#undef SUM9
            if (lane < 12) vec[24 + pr] = pack2(blo(a) * blo(b), bhi(a) * bhi(b));
            asm volatile("bar.arrive 8, %0;" ::"n"(32 * (NCW + 2)) : "memory");
        }
        if (cta < NRED && !half) {
            const float* q = reinterpret_cast<const float*>(smem + OFF_RED) + 12 * (lane & 7);
            bar_sync(6, 32 * (NCW + 1));
            const float4 a = *reinterpret_cast<const float4*>(q), b = *reinterpret_cast<const float4*>(q + 4);
            const float d = rbf((((a.x + a.y) + (a.z + a.w)) + ((b.x + b.y) + (b.z + b.w))) + q[8]);
            if (lane < 8) ptr.out[col] = __float2bfloat16_rn(x1 + rbf(gb * d));
            if (cta == 0 && lane == 0) { g_ticket = 0; g_epoch = tag; }
            if (lane == 0) TL(25);
        }
        return;
    }

    float* red = reinterpret_cast<float*>(smem + OFF_RED);
    float* stat = reinterpret_cast<float*>(smem + OFF_STAT);
    const int g = lane >> 2, tig = lane & 3;
    uint32_t cb1 = 0, sbp = 0;
    {
        const float xa = blo(xp), xb = bhi(xp);
        ln_stats_part(xa, xb, stat, warp, lane);
        if (has_mod) {
            const float ca = blo(cp), cb = bhi(cp);
            cp = pack2(ca * rcp(1.0f + ex2(-1.4426950408889634f * ca)), cb * rcp(1.0f + ex2(-1.4426950408889634f * cb)));
            mbar_wait(bars + 8 * (B_WMOD + (warp >> 1)), 0);
            gemv32(sb + OFF_WMOD + 4096 * warp, cp, red + 80 * warp, lane);
        }
        bar_sync(2, 32 * NCW);
        if (has_mod && warp == 0) red1(g_mod + 32 * (cta - MOD_C0) + lane, __float_as_uint(rbf(sum9(red + lane))) | tag);
        TL0(1);
        if (has_q) {
            float mean, rsd;
            ln_stats_fin(stat, mean, rsd);
            mbar_wait(bars + 8 * (B_WQ + (warp >> 1)), 0);
            uint2 sa, ca;
            uint32_t n = 0;
            do { sa = ldg2(g_mod + 2 * tid); ca = ldg2(g_mod + DM + 2 * tid); spin_guard(n); } while (bad2(sa, tag) | bad2(ca, tag));
            TL0(2);
            const uint32_t hp = ln_apply(xa, xb, mean, rsd, pack2(1.0f + untag(ca.x), 1.0f + untag(ca.y)), __byte_perm(sa.x, sa.y, 0x7632));
            __syncwarp();
            gemv32(sb + OFF_WQ + 4096 * warp, hp, red + 720 + 80 * warp, lane);
            bar_sync(2, 32 * NCW);
            if (warp == 0) red1(g_q + 32 * cta + lane, __float_as_uint(rbf(sum9(red + 720 + lane))) | tag);
            TL0(3);
        }
        {
            const int seg = tid >> 6;
            const int hd = seg == 0 ? head0 : seg == 1 ? head0 + 1 : HKV - 1;
            uint4 v = make_uint4(tag, tag, tag, tag);
            uint2 s2 = make_uint2(0, 0), c2 = s2;
            uint32_t n = 0;
            do {
                if (tid < 192) v = ldg4(g_q + 256 * hd + 4 * (tid & 63));
                if (bad2(s2, tag) | bad2(c2, tag)) { s2 = ldg2(g_mod + 3 * DM + 2 * tid); c2 = ldg2(g_mod + 4 * DM + 2 * tid); }
                spin_guard(n);
            } while (bad4(v, tag) | bad2(s2, tag) | bad2(c2, tag));
            if (tid < 192)
                *reinterpret_cast<uint2*>(smem + OFF_Q + 8 * tid) = make_uint2(__byte_perm(v.x, v.y, 0x7632), __byte_perm(v.z, v.w, 0x7632));
            sbp = __byte_perm(s2.x, s2.y, 0x7632);
            cb1 = pack2(1.0f + untag(c2.x), 1.0f + untag(c2.y));
        }
        bar_sync(2, 32 * NCW);
        TL0(4);
    }
    const uint32_t* sel = reinterpret_cast<const uint32_t*>(smem + OFF_SEL);

    if (warp < NAS) {
        const int r = lane & 7, var = r >> 2;
        const uint32_t kofs = (r + 8 * ((lane >> 3) & 1)) * 256, kx = (lane >> 4) ^ var ^ (2 * (r & 3));
        const uint32_t vofs = (r + 8 * (lane >> 4)) * 256, vx = ((lane >> 3) & 1) ^ var ^ (2 * (r & 3));
        const float bias = (tig == (g >> 2)) ? 0.f : -INFINITY;
        float* stage = reinterpret_cast<float*>(smem + OFF_STAGE);
        const uint32_t slot = sb + OFF_SLOT0 + ((warp + NAS - NAP) & (NAS - 1)) * (2 * ITEM);
        const uint32_t kb = slot + kofs, vb = slot + ITEM + vofs;
        const uint32_t kfull = bars + 16 * warp, kempty = kfull + 8 * B_EMPTY;
        int i = (warp - woff) & (NAS - 1);
        uint32_t ph = 0;
#pragma unroll 1
        for (int seg = 0; seg < 3; seg++) {
            if (seg == 1 && !last_seg) continue;
            if (seg == 2) {
                if (warp >= NAP) break;
                i = warp;
            }
            uint32_t qf[8][2];
            {
                const uint32_t* qs = reinterpret_cast<const uint32_t*>(smem + OFF_Q) + 128 * seg + 64 * (g & 1) + tig;
                const int qv = (g >> 1) & 1;
#pragma unroll
                for (int s = 0; s < 8; s++) { qf[s][0] = qs[8 * s + 4 * qv]; qf[s][1] = qs[8 * s + 4 * (qv ^ 1)]; }
            }
            float o[8][4] = {};
            float m0 = NEG_BIG, m1 = NEG_BIG, l0 = 0.f, l1 = 0.f;
            const int end = seg == 0 ? n0 : n01;
            const int nw = seg == 2 ? NAP : NAS;
#pragma unroll 1
            for (;; i += nw) {
                if (seg < 2) {
                    if (i >= end) break;
                    mbar_wait(kfull, ph);
                } else {
                    bool stop = false;
                    uint32_t n = 0;
                    while (true) {
                        if (i >= ntot[0]) { stop = true; break; }
                        if (mbar_test(kfull, ph)) break;
                        spin_guard(n);
                    }
                    if (__any_sync(0xffffffffu, stop)) break;
                }
                float s[2][2][4] = {};
#pragma unroll
                for (int st = 0; st < 8; st++) {
#pragma unroll
                    for (int mt = 0; mt < 2; mt++) {
                        uint32_t a[4];
                        ldsm4(kb + mt * 4096 + (st >> 2) * 128 + (((2 * (st & 3)) ^ (st >> 2) ^ kx) << 4), a);
                        mma16816(s[mt][st & 1], a, qf[st][0], qf[st][1]);
                    }
                }
                __syncwarp();
                if (lane == 0) mbar_arrive(kempty);
                float t[2][4];
#pragma unroll
                for (int mt = 0; mt < 2; mt++)
#pragma unroll
                    for (int j = 0; j < 4; j += 2) {
                        uint32_t p = pack2(s[mt][0][j] + s[mt][1][j], s[mt][0][j + 1] + s[mt][1][j + 1]);
                        p = pack2(blo(p) * 0.08838834764831845f, bhi(p) * 0.08838834764831845f);
                        t[mt][j] = fmaf(blo(p), 1.4426950408889634f, bias);
                        t[mt][j + 1] = fmaf(bhi(p), 1.4426950408889634f, bias);
                    }
                float x0 = fmaxf(fmaxf(t[0][0], t[0][2]), fmaxf(t[1][0], t[1][2]));
                float x1 = fmaxf(fmaxf(t[0][1], t[0][3]), fmaxf(t[1][1], t[1][3]));
                if (__any_sync(0xffffffffu, x0 > m0 || x1 > m1)) {
#pragma unroll
                    for (int d = 16; d; d >>= 1) {
                        x0 = fmaxf(x0, __shfl_xor_sync(0xffffffffu, x0, d));
                        x1 = fmaxf(x1, __shfl_xor_sync(0xffffffffu, x1, d));
                    }
                    x0 = fmaxf(x0, m0); x1 = fmaxf(x1, m1);
                    const float a0 = ex2(m0 - x0), a1 = ex2(m1 - x1);
                    m0 = x0; m1 = x1;
                    l0 *= a0; l1 *= a1;
#pragma unroll
                    for (int j = 0; j < 8; j++) { o[j][0] *= a0; o[j][1] *= a1; o[j][2] *= a0; o[j][3] *= a1; }
                }
                uint32_t pb[2][2];
#pragma unroll
                for (int mt = 0; mt < 2; mt++) {
                    const float p0 = ex2(t[mt][0] - m0), p1 = ex2(t[mt][1] - m1), p2 = ex2(t[mt][2] - m0), p3 = ex2(t[mt][3] - m1);
                    l0 += p0 + p2; l1 += p1 + p3;
                    pb[mt][0] = movmat(pack2(p0, p1));
                    pb[mt][1] = movmat(pack2(p2, p3));
                }
                mbar_wait(kfull + 8, ph);
                if (seg == 2) TLM(28);
#pragma unroll
                for (int mt = 0; mt < 2; mt++) {
#pragma unroll
                    for (int j = 0; j < 8; j++) {
                        uint32_t a[4];
                        ldsm4t(vb + mt * 4096 + (j >> 2) * 128 + (((2 * (j & 3)) ^ (j >> 2) ^ vx) << 4), a);
                        mma16816(o[j], a, pb[mt][0], pb[mt][1]);
                    }
                }
                __syncwarp();
                if (lane == 0) mbar_arrive(kempty + 8);
                ph ^= 1;
            }
            if (seg == 2) TLM(5);
            l0 += __shfl_xor_sync(0xffffffffu, l0, 17); l1 += __shfl_xor_sync(0xffffffffu, l1, 17);
            float* sw = stage + 260 * warp;
#pragma unroll
            for (int j = 0; j < 8; j++) {
                const float u0 = o[j][0] + __shfl_xor_sync(0xffffffffu, o[j][2], 1);
                const float u1 = o[j][1] + __shfl_xor_sync(0xffffffffu, o[j][3], 1);
                if (tig < 2) { sw[16 * j + 8 * tig + g] = u0; sw[128 + 16 * j + 8 * tig + g] = u1; }
                if (j == 2 || j == 5) {
                    l0 += __shfl_xor_sync(0xffffffffu, l0, j == 2 ? 4 : 8);
                    l1 += __shfl_xor_sync(0xffffffffu, l1, j == 2 ? 4 : 8);
                }
            }
            if (lane == 0) *reinterpret_cast<float4*>(sw + 256) = make_float4(m0, l0, m1, l1);
            bar_sync(1, 32 * nw);
            if (tid == 128 && seg >= last_seg) mbar_arrive(bars + 8 * (seg == 2 ? B_PDONE : B_SDONE));
            if (tid < 128) {
                const int h = tid >> 6;
                float2 ml[NAS], ov[NAS];
                float M = NEG_BIG;
#pragma unroll
                for (int w = 0; w < NAS; w++) {
                    ml[w] = make_float2(NEG_BIG, 0.f); ov[w] = make_float2(0.f, 0.f);
                    if (w < NAP || seg < 2) {
                        ml[w] = *reinterpret_cast<const float2*>(stage + 260 * w + 256 + 2 * h);
                        ov[w] = *reinterpret_cast<const float2*>(stage + 260 * w + 2 * tid);
                    }
                    M = fmaxf(M, ml[w].x);
                }
                float a = 0.f, b = 0.f, L = 0.f;
#pragma unroll
                for (int w = 0; w < NAS; w++) {
                    const float e = ex2(ml[w].x - M);
                    a += e * ov[w].x; b += e * ov[w].y; L += e * ml[w].y;
                }
                const uint32_t w0 = tagw(M, tag), w1 = (__float_as_uint(M) << 2) | tag, w2 = tagw(L, tag);
                if (seg == 2) {
                    const int p = tid >> 4, k = cta / 28;
                    uint32_t* q = mbox(BOX_P + 5 * p + k, sel[NRED + p] >> k);
                    stg2(q + 32 * (cta % 28) + 2 * (tid & 15), tagw(a, tag), tagw(b, tag));
                    if ((tid & 15) == 0) stg4(q + 896 + 4 * (cta % 28), w0, w1, w2, w2);
                } else {
                    stg2(g_part + (cta * 2 + seg) * 256 + 2 * tid, tagw(a, tag), tagw(b, tag));
                    if ((tid & 63) == 0) stg4(g_ml + ((seg * 2 + h) * 144 + cta) * 4, w0, w1, w2, w2);
                }
            }
            if (seg < 2) { if (seg == last_seg) bar_sync(3, 32 * (NCW + 2)); else bar_sync(1, 32 * NAS); }
        }
        TL0(6);
    } else {
        bar_sync(3, 32 * (NCW + 2));
    }
    const int r0 = 8 * warp + 2 * tig;
    const uint32_t sel0 = sel[r0], sel1 = sel[r0 + 1];
#define PUBLISH_Y(j)                                                        \
    do {                                                                    \
        stg1(mbox(2 * r0, sel0) + 8 * (j) + g, tagw(v0, tag));               \
        stg1(mbox(2 * r0 + 2, sel1) + 8 * (j) + g, tagw(v1, tag));           \
    } while (0)

    uint32_t* vec = reinterpret_cast<uint32_t*>(smem + OFF_VEC);
    if (stat_wo) {
        const int u = tid - 32 * NAP;
        if (u >= 0 && u < 40) {
            const int row = 40 * cta + u, kvh = row >> 8, h = (row >> 7) & 1;
            int q = (kvh * TPH * NG) / NSTATIC;
            while (group_begin(q + 1) <= kvh * TPH) q++;
            while (group_begin(q) > kvh * TPH) q--;
            float M = NEG_BIG, num = 0.f, den = 0.f;
#pragma unroll 1
            for (; group_begin(q) < (kvh + 1) * TPH; q++) {
                const int seg = group_begin(q) / TPH == kvh ? 0 : 1;
                uint4 ml[GRP];
                uint32_t ov[GRP], bad, spin = 0;
                while (true) {
                    bad = 0;
#pragma unroll
                    for (int k = 0; k < GRP; k++) {
                        ov[k] = ldg1(g_part + ((GRP * q + k) * 2 + seg) * 256 + (row & 255));
                        ml[k] = ldg4(g_ml + ((seg * 2 + h) * 144 + GRP * q + k) * 4);
                    }
#pragma unroll
                    for (int k = 0; k < GRP; k++) bad |= bad4(ml[k], tag) | ((ov[k] ^ tag) & 3u);
                    if (!bad) break;
                    __nanosleep(300);
                    spin_guard(spin);
                }
#pragma unroll
                for (int k = 0; k < GRP; k++) {
                    const float m = __uint_as_float((ml[k].x & ~3u) | ((ml[k].y >> 2) & 3u)), Mn = fmaxf(M, m);
                    const float e0 = ex2(M - Mn), e1 = ex2(m - Mn);
                    num = num * e0 + e1 * untag(ov[k]);
                    den = den * e0 + e1 * untag(ml[k].z);
                    M = Mn;
                }
            }
            reinterpret_cast<uint16_t*>(vec)[u] = (uint16_t)pack2(num * rcp(den), 0.f);
        }
        bar_sync(2, 32 * NCW);
        float c[4][4] = {};
#pragma unroll
        for (int s = 0; s < 3; s++) {
            const uint32_t b0 = vec[8 * s + tig], b1 = s < 2 ? vec[8 * s + 4 + tig] : 0u;
            uint32_t a[4][4];
            mbar_wait(bars + 8 * (B_WO + 2 * s), 0);
            if (s < 2) mbar_wait(bars + 8 * (B_WO + 2 * s + 1), 0);
            load_frags64(sb + OFF_WO, s, s == 2, warp, lane, a);
#pragma unroll
            for (int i = 0; i < 4; i++) mma16816(c[i], a[i], b0, b1);
        }
        float v0, v1;
        pick2(c, tig, v0, v1);
        PUBLISH_Y(cta);
        TLM(7);
    } else if (pool_head) {
        uint32_t wa[2][4][4];
#pragma unroll
        for (int s = 0; s < 2; s++) {
            mbar_wait(bars + 8 * (B_WO + 2 * s), 0);
            mbar_wait(bars + 8 * (B_WO + 2 * s + 1), 0);
            load_frags64(sb + OFF_WO, s, false, warp, lane, wa[s]);
        }
        const int c0 = 16 * warp + (lane >> 3);
        const uint32_t* po[4];
        uint32_t mo[4];
#pragma unroll
        for (int k = 0; k < 4; k++) {
            const int c = min(c0 + 4 * k, NCTA - 1), b = c / 28, j = c % 28;
            po[k] = mbox(BOX_P + 5 * (cta - C_P) + b, sel[NRED + cta - C_P] >> b) + 32 * j + 4 * (lane & 7);
            mo[k] = 896 + 4 * j - 32 * j - 4 * (lane & 7);
        }
        if (E1_WAIT > 0.f) {
            mbar_wait(bars + 8 * B_PDONE, 0);
            const uint32_t go = (uint32_t)ntot[2];
            uint32_t n = 0;
            while ((int)(clk() - go) < 0) spin_guard(n);
        } else if (warp >= NAP) mbar_wait(bars + 8 * B_PDONE, 0);
        uint4 ov[4], ml[4];
#pragma unroll
        for (int k = 0; k < 4; k++) {
            const uint32_t w = c0 + 4 * k < NCTA ? 0 : tag;
            ov[k] = make_uint4(w, w, w, w);
            ml[k] = make_uint4(tagw(NEG_BIG, tag), w, w, w);
        }
        uint32_t bad, spin = 0;
        do {
#pragma unroll
            for (int k = 0; k < 4; k++) {
                if (bad4(ov[k], tag)) ov[k] = ldg4(po[k]);
                if (bad4(ml[k], tag)) ml[k] = ldg4(po[k] + mo[k]);
            }
            bad = 0;
#pragma unroll
            for (int k = 0; k < 4; k++) bad |= bad4(ov[k], tag) | bad4(ml[k], tag);
            spin_guard(spin);
        } while (bad);
        __syncwarp();
        TLM(29);
        float mk[4];
#pragma unroll
        for (int k = 0; k < 4; k++) mk[k] = __uint_as_float((ml[k].x & ~3u) | ((ml[k].y >> 2) & 3u));
        float M = fmaxf(fmaxf(mk[0], mk[1]), fmaxf(mk[2], mk[3]));
        M = fmaxf(M, __shfl_xor_sync(0xffffffffu, M, 8));
        M = fmaxf(M, __shfl_xor_sync(0xffffffffu, M, 16));
        float a[5] = {};
#pragma unroll
        for (int k = 0; k < 4; k++) {
            const float e = ex2(mk[k] - M);
            a[0] += e * untag(ov[k].x); a[1] += e * untag(ov[k].y); a[2] += e * untag(ov[k].z); a[3] += e * untag(ov[k].w);
            a[4] += e * untag(ml[k].z);
        }
#pragma unroll
        for (int j = 0; j < 5; j++) a[j] += __shfl_xor_sync(0xffffffffu, a[j], 8);
#pragma unroll
        for (int j = 0; j < 5; j++) a[j] += __shfl_xor_sync(0xffffffffu, a[j], 16);
        if (lane < 8) *reinterpret_cast<float4*>(red + 40 * warp + 4 * lane) = make_float4(a[0], a[1], a[2], a[3]);
        if (lane == 0) *reinterpret_cast<float2*>(red + 40 * warp + 32) = make_float2(M, a[4]);
        if (warp < NCW - 1) {
            asm volatile("bar.arrive 7, %0;" ::"n"(32 * NCW) : "memory");
        } else {
            bar_sync(7, 32 * NCW);
            float2 sw[NCW];
            float ow[NCW], MM = NEG_BIG;
#pragma unroll
            for (int w = 0; w < NCW; w++) {
                sw[w] = *reinterpret_cast<const float2*>(red + 40 * w + 32);
                ow[w] = red[40 * w + lane];
                MM = fmaxf(MM, sw[w].x);
            }
            float num[2] = {}, den[2] = {};
#pragma unroll
            for (int w = 0; w < NCW; w++) { const float e = ex2(sw[w].x - MM); num[w & 1] += e * ow[w]; den[w & 1] += e * sw[w].y; }
            reinterpret_cast<uint16_t*>(vec)[lane] = (uint16_t)pack2((num[0] + num[1]) * rcp(den[0] + den[1]), 0.f);
            if (lane == 0) TL(13);
        }
        bar_sync(2, 32 * NCW);
        float c[4][4] = {};
#pragma unroll
        for (int s = 0; s < 2; s++) {
            const uint32_t b0 = vec[8 * s + tig], b1 = vec[8 * s + 4 + tig];
#pragma unroll
            for (int i = 0; i < 4; i++) mma16816(c[i], wa[s][i], b0, b1);
        }
        float v0, v1;
        pick2(c, tig, v0, v1);
        PUBLISH_Y(cta - (C_P - C_X));
        TLM(8);
    }

    {
        uint32_t ga[4][6][4];
        const int r = lane & 7, mhi = (lane >> 3) & 1, khi = lane >> 4;
        const uint32_t box = sb + (mhi ? OFF_UP : OFF_GATE) + 4096 * warp + (8 * khi + r) * 64;
        const uint32_t boxx = sb + (mhi ? OFF_UPX : OFF_GATEX) + 2048 * warp + (8 * khi + r) * 32;
#define LOAD_GU()                                                           \
        do {                                                                \
            _Pragma("unroll") for (int s = 0; s < 4; s++)                   \
                _Pragma("unroll") for (int i = 0; i < 4; i++) ldsm4t(box + s * 1024 + ((i ^ (r >> 1)) << 4), ga[s][i]); \
            if (extra) {                                                    \
                _Pragma("unroll") for (int s = 0; s < 4; s++)               \
                    _Pragma("unroll") for (int i = 0; i < 2; i++) ldsm4t(boxx + s * 512 + ((i ^ (r >> 2)) << 4), ga[s][4 + i]); \
            }                                                               \
        } while (0)
        const int gate = TIMED || stat_wo || extra ? X1_GATE : 8;
        mbar_wait(bars + 8 * (B_GU + min(warp, gate)), 0);
        bool have = false;
        const uint32_t* px = mbox(BOX_X + (cta & 3), sel[80]) + 2 * tid;
        uint2 xv = make_uint2(0, 0);
        uint32_t n = 0;
        while (true) {
            if (!have && __all_sync(0xffffffffu, mbar_test(bars + 8 * (B_GU + warp), 0))) {
                have = true;
                LOAD_GU();
            }
            if (n == 0) mbar_wait(bars + 8 * (B_GU + gate), 0);
            if (bad2(xv, tag)) xv = ldg2(px);
            if (!__any_sync(0xffffffffu, bad2(xv, tag))) break;
            spin_guard(n);
        }
        TLM(15);
        const float xa = untag(xv.x), xb = untag(xv.y);
        ln_stats_part(xa, xb, stat + 20, warp, lane);
        bar_sync(2, 32 * NCW);
        if (tid == 0) ntot[1] = 1;
        TL0(9);
        float mean, rsd;
        ln_stats_fin(stat + 20, mean, rsd);
        const uint32_t hp = ln_apply(xa, xb, mean, rsd, cb1, sbp);
        if (!have) {
            mbar_wait(bars + 8 * (B_GU + warp), 0);
            LOAD_GU();
        }
        if (tid == 256) TL(14);
        float c[6][4] = {};
        uint32_t b[4][2];
#pragma unroll
        for (int s = 0; s < 4; s++) {
            b[s][0] = __shfl_sync(0xffffffffu, hp, 8 * s + tig);
            b[s][1] = __shfl_sync(0xffffffffu, hp, 8 * s + 4 + tig);
#pragma unroll
            for (int i = 0; i < 4; i++) mma16816(c[i], ga[s][i], b[s][0], b[s][1]);
        }
        if (extra) {
#pragma unroll
            for (int s = 0; s < 4; s++)
#pragma unroll
                for (int i = 4; i < 6; i++) mma16816(c[i], ga[s][i], b[s][0], b[s][1]);
        }
        float* rw = red + 720 + 96 * warp + 48 * (tig & 1) + 8 * (tig >> 1) + g;
#pragma unroll
        for (int i = 0; i < 6; i += 2) {
            const float lo = (tig & 1) ? c[i][2] : c[i][0], hi = (tig & 1) ? c[i + 1][2] : c[i + 1][0];
            rw[8 * i] = (tig & 2) ? hi : lo;
        }
    }
    asm volatile("bar.arrive 4, %0;" ::"n"(32 * (NCW + 2)) : "memory");

    uint32_t da[3][4][4];
    const int zb = cta >= ZA, zo = 8 * (zb ? cta - ZA : NY + cta) + g;
    uint32_t* const z0 = mbox(2 * r0 + zb, sel0 >> zb) + zo;
    uint32_t* const z1 = mbox(2 * r0 + 2 + zb, sel1 >> zb) + zo;
    const int rb = tid >= 2 * ZA;
    const uint32_t* const zr = mbox(2 * cta + rb, sel[min(cta, NRED - 1)] >> rb) + 4 * (rb ? tid - 2 * ZA : 2 * NY + tid);
    const uint32_t ok = __ballot_sync(0xffffffffu, lane < 3 && mbar_test(bars + 8 * (B_DOWN + min(lane, 2)), 0));
    const int nd = !(ok & 1u) ? 0 : !(ok & 2u) ? 1 : !(ok & 4u) ? 2 : 3;
    __syncwarp();
#pragma unroll
    for (int s = 0; s < 3; s++) if (s < nd) load_frags64(sb + OFF_DOWN, s, false, warp, lane, da[s]);
    bar_sync(8, 32 * (NCW + 2));
    TL0(10);
    {
        float c[4][4] = {};
#pragma unroll
        for (int s = 0; s < 3; s++) {
            if (s == 2 && !extra) break;
            const uint32_t b0 = vec[24 + 8 * s + tig], b1 = vec[24 + 8 * s + 4 + tig];
            if (s >= nd) {
                mbar_wait(bars + 8 * (B_DOWN + s), 0);
                load_frags64(sb + OFF_DOWN, s, false, warp, lane, da[s]);
            }
#pragma unroll
            for (int i = 0; i < 4; i++) mma16816(c[i], da[s][i], b0, b1);
        }
        float v0, v1;
        pick2(c, tig, v0, v1);
        stg1(z0, tagw(v0, tag));
        stg1(z1, tagw(v1, tag));
        TLM(11);
    }
    if (cta < NRED) {
        uint4 v = make_uint4(tag, tag, tag, tag);
        if (tid < 2 * NCTA) {
            uint32_t n = 0;
            do { v = ldg4(zr); spin_guard(n); } while (bad4(v, tag));
        }
        __syncwarp();
        TLM(31);
        const float k = warp_cols(untag(v.x), untag(v.y), untag(v.z), untag(v.w), lane);
        if (lane < 8) red[12 * lane + warp] = k;
        asm volatile("bar.arrive 6, %0;" ::"n"(32 * (NCW + 1)) : "memory");
    }
}

typedef CUresult (*EncodeFn)(CUtensorMap*, CUtensorMapDataType, cuuint32_t, void*, const cuuint64_t*, const cuuint64_t*,
                             const cuuint32_t*, const cuuint32_t*, CUtensorMapInterleave, CUtensorMapSwizzle,
                             CUtensorMapL2promotion, CUtensorMapFloatOOBfill);

void make_map(EncodeFn enc, CUtensorMap* m, void* p, uint64_t cols, uint64_t rows, uint32_t bc, uint32_t br, CUtensorMapSwizzle sw, int promo = 0) {
    cuuint64_t gd[2] = {cols, rows};
    cuuint64_t gs[1] = {cols * 2};
    cuuint32_t bd[2] = {bc, br};
    cuuint32_t es[2] = {1, 1};
    enc(m, CU_TENSOR_MAP_DATA_TYPE_BFLOAT16, 2, p, gd, gs, bd, es, CU_TENSOR_MAP_INTERLEAVE_NONE, sw,
        (CUtensorMapL2promotion)promo, CU_TENSOR_MAP_FLOAT_OOB_FILL_NONE);
}

}

extern "C" void kernel_launch(void* const* d_in, const int* in_sizes, int n_in, void* d_out, int out_size) {
    (void)in_sizes; (void)n_in; (void)out_size;
    EncodeFn enc = nullptr;
    cudaDriverEntryPointQueryResult qr;
    cudaGetDriverEntryPoint("cuTensorMapEncodeTiled", (void**)&enc, cudaEnableDefault, &qr);
    Maps maps;
    make_map(enc, &maps.k, d_in[1], 64, (uint64_t)HKV * SK * 2, 64, 2 * TILE, CU_TENSOR_MAP_SWIZZLE_128B);
    make_map(enc, &maps.v, d_in[2], 64, (uint64_t)HKV * SK * 2, 64, 2 * TILE, CU_TENSOR_MAP_SWIZZLE_128B);
    make_map(enc, &maps.wmod, d_in[10], 6 * DM, DM, 32, 64, CU_TENSOR_MAP_SWIZZLE_64B);
    make_map(enc, &maps.wq, d_in[3], 4096, DM, 32, 64, CU_TENSOR_MAP_SWIZZLE_64B);
    make_map(enc, &maps.wo, d_in[4], 64, 4096 * 9, 64, 72, CU_TENSOR_MAP_SWIZZLE_128B);
    make_map(enc, &maps.gate, d_in[6], FF, DM, 32, 64, CU_TENSOR_MAP_SWIZZLE_64B, GU_PROMO);
    make_map(enc, &maps.up, d_in[7], FF, DM, 32, 64, CU_TENSOR_MAP_SWIZZLE_64B, GU_PROMO);
    make_map(enc, &maps.gatex, d_in[6], FF, DM, 16, 64, CU_TENSOR_MAP_SWIZZLE_32B, GU_PROMO);
    make_map(enc, &maps.upx, d_in[7], FF, DM, 16, 64, CU_TENSOR_MAP_SWIZZLE_32B, GU_PROMO);
    make_map(enc, &maps.down, d_in[8], 64, FF * 9, 64, 72, CU_TENSOR_MAP_SWIZZLE_128B);
    cudaFuncSetAttribute(fused_kernel, cudaFuncAttributeMaxDynamicSharedMemorySize, SMEM_BYTES);
    typedef const __nv_bfloat16* P;
    const Ptrs ptr = {(P)d_in[1], (P)d_in[0], (P)d_in[9], (__nv_bfloat16*)d_out};
    fused_kernel<<<NCTA, NTHREADS, SMEM_BYTES, cudaStreamPerThread>>>(ptr, maps);
}
```

```cpp
#include <cuda_runtime.h>
#include <cuda_bf16.h>
#include <cuda.h>
#include <stdint.h>

namespace {

constexpr int DM = 576;
constexpr int SK = 65536;
constexpr int HKV = 16;
constexpr int FF = 4608;
constexpr int NCTA = 132;
constexpr int NQ = 128;
constexpr int MOD_C0 = 42;
constexpr int NRED = 72;
constexpr int C_X = 96, C_P = 120, C_E = 128;
constexpr int NY = C_X + (C_E - C_P);
constexpr int FX0 = 32 * NCTA;
static_assert(FX0 + 16 * (C_P - C_X) == FF && 40 * C_X == 256 * (HKV - 1), "weight split");

constexpr int TILE = 32;
constexpr int TPH = SK / TILE;
constexpr int NSTATIC = (HKV - 1) * TPH;
constexpr int GRP = 4;
constexpr int NG = NCTA / GRP;
constexpr int NPOOL = TPH;
constexpr int ITEM = TILE * 256;

constexpr int D_PRO = 5, N_PRO = 32;
constexpr int D_MAIN = 6;
constexpr int D_POOL = 5;
constexpr int D_CAP = 6;
constexpr int DMAX = 6;
constexpr float T_LEAD = 1.1f;
constexpr float T_GB = 0.3f;
constexpr int X1_GATE = 6;
constexpr int PF_BYTES = 8192;
constexpr int NPROBE = 14;

constexpr int NCW = 9;
constexpr int NAS = 8;
constexpr int NAP = 5;
constexpr int W_PROD = 9, W_RED = 10;
constexpr int NTHREADS = 12 * 32;

constexpr int OFF_WMOD = 0;
constexpr int OFF_WQ = 9 * 4096;
constexpr int OFF_WO = 0;
constexpr int OFF_GATEX = 0;
constexpr int OFF_UPX = 9 * 2048;
constexpr int OFF_GATE = 40 * 1152;
constexpr int OFF_UP = OFF_GATE + 9 * 4096;
constexpr int OFF_SLOT0 = 18 * 4096;
constexpr int OFF_RING = OFF_SLOT0 + 2 * (NAS - NAP) * ITEM;
constexpr int OFF_DOWN = OFF_RING;
constexpr int OFF_GB = OFF_DOWN + 48 * 1152;
constexpr int OFF_BAR = OFF_RING + 2 * NAP * ITEM;
constexpr int OFF_STAGE = OFF_BAR + 512;
constexpr int OFF_RED = OFF_STAGE + NAS * 260 * 4;
constexpr int OFF_Q = OFF_RED + 9 * (80 + 96) * 4;
constexpr int OFF_STAT = OFF_Q + 3 * 256 * 2;
constexpr int OFF_VEC = OFF_STAT + 2 * 20 * 4;
constexpr int OFF_SEL = OFF_VEC + 64 * 4;
constexpr int OFF_SILU = OFF_SEL + 96 * 4;
constexpr int OFF_NTOT = OFF_SILU + DM * 2;
constexpr int SMEM_BYTES = OFF_NTOT + 16;
static_assert(SMEM_BYTES <= 232448, "smem");
static_assert(OFF_UP + 9 * 4096 <= OFF_RING && OFF_GATE % 1024 == 0, "layout");

constexpr int B_EMPTY = 2 * NAS, B_WO = 4 * NAS, B_GU = B_WO + 5, B_DOWN = B_GU + 9, B_SDONE = B_DOWN + 3, B_PDONE = B_SDONE + 1,
              B_GB = B_PDONE + 1, B_SEL = B_GB + 1, B_Q2 = B_SEL + 1, B_WMOD = B_Q2 + 1, B_WQ = B_WMOD + 5, B_END = B_WQ + 5;
static_assert(B_END <= 64, "barriers");

constexpr float NEG_BIG = -3.0e38f;
constexpr uint32_t SPIN_LIMIT = 1u << 20;

struct Maps { CUtensorMap wmod, wq, k, v, wo, gate, up, gatex, upx, down, gb; };

__device__ uint32_t g_epoch;
__device__ __align__(128) uint32_t g_ticket[8];
__device__ __align__(128) uint32_t g_mod[5 * DM];
__device__ __align__(128) uint32_t g_q[4096];
__device__ __align__(128) uint32_t g_part[NCTA * 2 * 2 * 128];
__device__ __align__(128) uint32_t g_ml[2 * 2 * 144 * 4];
constexpr int BOX_P = 2 * NRED, BOX_X = BOX_P + 5 * 8, NBOX = BOX_X + 4;
constexpr int ZA = 20;
__device__ __align__(128) uint32_t g_boxes[(NBOX + 1) * 2048];
__device__ __align__(128) uint32_t g_sel[NRED + 8];

__device__ __forceinline__ void mbar_init(uint32_t b, uint32_t c) {
    asm volatile("mbarrier.init.shared::cta.b64 [%0], %1;" ::"r"(b), "r"(c) : "memory");
}
__device__ __forceinline__ void mbar_expect(uint32_t b, uint32_t bytes) {
    asm volatile("mbarrier.arrive.expect_tx.shared::cta.b64 _, [%0], %1;" ::"r"(b), "r"(bytes) : "memory");
}
__device__ __forceinline__ void mbar_arrive(uint32_t b) {
    asm volatile("mbarrier.arrive.shared::cta.b64 _, [%0];" ::"r"(b) : "memory");
}
__device__ __forceinline__ bool mbar_try(uint32_t b, uint32_t ph) {
    uint32_t ok;
    asm volatile("{\n.reg .pred p;\nmbarrier.try_wait.parity.shared::cta.b64 p, [%1], %2;\nselp.u32 %0, 1, 0, p;\n}"
                 : "=r"(ok) : "r"(b), "r"(ph) : "memory");
    return ok;
}
__device__ __forceinline__ bool mbar_test(uint32_t b, uint32_t ph) {
    uint32_t ok;
    asm volatile("{\n.reg .pred p;\nmbarrier.test_wait.parity.shared::cta.b64 p, [%1], %2;\nselp.u32 %0, 1, 0, p;\n}"
                 : "=r"(ok) : "r"(b), "r"(ph) : "memory");
    return ok;
}
__device__ __forceinline__ void mbar_wait(uint32_t b, uint32_t ph) {
    uint32_t n = 0;
    while (!mbar_try(b, ph)) { if (++n > SPIN_LIMIT) __trap(); }
}
__device__ __forceinline__ void tma2d(uint32_t dst, const CUtensorMap* m, int c0, int c1, uint32_t bar, uint64_t pol) {
    asm volatile("cp.async.bulk.tensor.2d.shared::cluster.global.mbarrier::complete_tx::bytes.L2::cache_hint "
                 "[%0], [%1, {%3, %4}], [%2], %5;"
                 ::"r"(dst), "l"(m), "r"(bar), "r"(c0), "r"(c1), "l"(pol) : "memory");
}
__device__ __forceinline__ void bar_sync(int id, int n) { asm volatile("bar.sync %0, %1;" ::"r"(id), "r"(n) : "memory"); }
__device__ __forceinline__ void ldsm4(uint32_t a, uint32_t (&r)[4]) {
    asm volatile("ldmatrix.sync.aligned.m8n8.x4.shared.b16 {%0,%1,%2,%3}, [%4];"
                 : "=r"(r[0]), "=r"(r[1]), "=r"(r[2]), "=r"(r[3]) : "r"(a) : "memory");
}
__device__ __forceinline__ void ldsm4t(uint32_t a, uint32_t (&r)[4]) {
    asm volatile("ldmatrix.sync.aligned.m8n8.x4.trans.shared.b16 {%0,%1,%2,%3}, [%4];"
                 : "=r"(r[0]), "=r"(r[1]), "=r"(r[2]), "=r"(r[3]) : "r"(a) : "memory");
}
__device__ __forceinline__ void mma16816(float (&c)[4], const uint32_t (&a)[4], uint32_t b0, uint32_t b1) {
    asm volatile("mma.sync.aligned.m16n8k16.row.col.f32.bf16.bf16.f32 {%0,%1,%2,%3}, {%4,%5,%6,%7}, {%8,%9}, {%0,%1,%2,%3};"
                 : "+f"(c[0]), "+f"(c[1]), "+f"(c[2]), "+f"(c[3])
                 : "r"(a[0]), "r"(a[1]), "r"(a[2]), "r"(a[3]), "r"(b0), "r"(b1));
}
__device__ __forceinline__ uint32_t movmat(uint32_t a) {
    uint32_t d; asm volatile("movmatrix.sync.aligned.m8n8.trans.b16 %0, %1;" : "=r"(d) : "r"(a)); return d;
}
__device__ __forceinline__ float ex2(float x) { float y; asm("ex2.approx.ftz.f32 %0, %1;" : "=f"(y) : "f"(x)); return y; }
__device__ __forceinline__ uint32_t pack2(float lo, float hi) {
    uint32_t r; asm("cvt.rn.bf16x2.f32 %0, %1, %2;" : "=r"(r) : "f"(hi), "f"(lo)); return r;
}
__device__ __forceinline__ float rbf(float x) { return __uint_as_float(pack2(0.f, x)); }
__device__ __forceinline__ float rcp(float x) { float y; asm("rcp.approx.ftz.f32 %0, %1;" : "=f"(y) : "f"(x)); return y; }
__device__ __forceinline__ float blo(uint32_t p) { return __uint_as_float(p << 16); }
__device__ __forceinline__ float bhi(uint32_t p) { return __uint_as_float(p & 0xffff0000u); }

__device__ __forceinline__ uint32_t tagw(float v, uint32_t tag) { return (__float_as_uint(v) & ~3u) | tag; }
__device__ __forceinline__ float untag(uint32_t w) { return __uint_as_float(w & ~3u); }
__device__ __forceinline__ void stg1(uint32_t* p, uint32_t a) {
    asm volatile("st.relaxed.gpu.global.u32 [%0], %1;" ::"l"(p), "r"(a) : "memory");
}
__device__ __forceinline__ void stg2(uint32_t* p, uint32_t a, uint32_t b) {
    asm volatile("st.relaxed.gpu.global.v2.u32 [%0], {%1,%2};" ::"l"(p), "r"(a), "r"(b) : "memory");
}
__device__ __forceinline__ void stg4(uint32_t* p, uint32_t a, uint32_t b, uint32_t c, uint32_t d) {
    asm volatile("st.relaxed.gpu.global.v4.u32 [%0], {%1,%2,%3,%4};" ::"l"(p), "r"(a), "r"(b), "r"(c), "r"(d) : "memory");
}
__device__ __forceinline__ void red1(uint32_t* p, uint32_t a) {
    asm volatile("red.relaxed.gpu.global.or.b32 [%0], %1;" ::"l"(p), "r"(a) : "memory");
}
__device__ __forceinline__ uint32_t ldg1(const uint32_t* p) {
    uint32_t v; asm volatile("ld.relaxed.gpu.global.u32 %0, [%1];" : "=r"(v) : "l"(p) : "memory"); return v;
}
__device__ __forceinline__ uint2 ldg2(const uint32_t* p) {
    uint2 v; asm volatile("ld.relaxed.gpu.global.v2.u32 {%0,%1}, [%2];" : "=r"(v.x), "=r"(v.y) : "l"(p) : "memory"); return v;
}
__device__ __forceinline__ uint4 ldg4(const uint32_t* p) {
    uint4 v;
    asm volatile("ld.relaxed.gpu.global.v4.u32 {%0,%1,%2,%3}, [%4];" : "=r"(v.x), "=r"(v.y), "=r"(v.z), "=r"(v.w) : "l"(p) : "memory");
    return v;
}
__device__ __forceinline__ uint32_t bad2(uint2 v, uint32_t tag) { return ((v.x ^ tag) | (v.y ^ tag)) & 3u; }
__device__ __forceinline__ uint32_t bad4(uint4 v, uint32_t tag) {
    return ((v.x ^ tag) | (v.y ^ tag) | (v.z ^ tag) | (v.w ^ tag)) & 3u;
}
__device__ __forceinline__ uint32_t clk() { uint32_t c; asm volatile("mov.u32 %0, %%clock;" : "=r"(c)); return c; }
__device__ __forceinline__ void spin_guard(uint32_t& n) { if (++n > SPIN_LIMIT) __trap(); }

__device__ __forceinline__ void ln_stats_part(float a, float b, float* stat, int warp, int lane) {
    float s = a + b, q = a * a + b * b;
#pragma unroll
    for (int o = 16; o; o >>= 1) { s += __shfl_xor_sync(0xffffffffu, s, o); q += __shfl_xor_sync(0xffffffffu, q, o); }
    if (lane == 0) *reinterpret_cast<float2*>(stat + 2 * warp) = make_float2(s, q);
}
__device__ __forceinline__ void ln_stats_fin(const float* stat, float& mean, float& rsd) {
    const float4 a = *reinterpret_cast<const float4*>(stat), b = *reinterpret_cast<const float4*>(stat + 4),
                 c = *reinterpret_cast<const float4*>(stat + 8), d = *reinterpret_cast<const float4*>(stat + 12);
    const float2 e = *reinterpret_cast<const float2*>(stat + 16);
    const float mu = (((a.x + a.z) + (b.x + b.z)) + ((c.x + c.z) + (d.x + d.z)) + e.x) * (1.0f / DM);
    const float sq = (((a.y + a.w) + (b.y + b.w)) + ((c.y + c.w) + (d.y + d.w)) + e.y) * (1.0f / DM);
    mean = rbf(mu);
    const float v = rbf(rbf(fmaxf(fmaf(-mu, mu, sq), 0.f)) + 1e-5f);
    float sd;
    asm("sqrt.approx.ftz.f32 %0, %1;" : "=f"(sd) : "f"(v));
    rsd = rcp(rbf(sd));
}
__device__ __forceinline__ uint32_t ln_apply(float xa, float xb, float mean, float rsd, uint32_t scale1, uint32_t shift) {
    uint32_t p = pack2(xa - mean, xb - mean);
    p = pack2(blo(p) * rsd, bhi(p) * rsd);
    p = pack2(blo(p) * blo(scale1), bhi(p) * bhi(scale1));
    return pack2(blo(p) + blo(shift), bhi(p) + bhi(shift));
}

__device__ __forceinline__ void gemv32(uint32_t box, uint32_t vp, float* red, int lane) {
    const int r = lane & 7, mhi = (lane >> 3) & 1, khi = lane >> 4, tig = lane & 3, g = lane >> 2;
    float c[2][2][4] = {};
#pragma unroll
    for (int s = 0; s < 4; s++) {
        uint32_t b0 = __shfl_sync(0xffffffffu, vp, 8 * s + tig), b1 = __shfl_sync(0xffffffffu, vp, 8 * s + 4 + tig);
        const int row = 16 * s + 8 * khi + r;
#pragma unroll
        for (int i = 0; i < 2; i++) {
            uint32_t a[4];
            ldsm4t(box + row * 64 + (((2 * i + mhi) ^ (r >> 1)) << 4), a);
            mma16816(c[i][s & 1], a, b0, b1);
        }
    }
    const float v0 = (tig & 1) ? c[0][0][2] + c[0][1][2] : c[0][0][0] + c[0][1][0];
    const float v1 = (tig & 1) ? c[1][0][2] + c[1][1][2] : c[1][0][0] + c[1][1][0];
    red[8 * tig + g] = (tig & 2) ? v1 : v0;
}
__device__ __forceinline__ float sum9(const float* p) {
    return (((p[0] + p[80]) + (p[160] + p[240])) + ((p[320] + p[400]) + (p[480] + p[560]))) + p[640];
}

__device__ __forceinline__ void load_frags64(uint32_t base, int s, bool half, int w, int lane, uint32_t (&a)[4][4]) {
    const int r = lane & 7, mhi = (lane >> 3) & 1, khi = half ? 0 : lane >> 4;
    const int row = 16 * s + 8 * khi + r;
    const uint32_t line = base + (9 * row + w) * 128, x = mhi ^ ((row + w) & 7);
#pragma unroll
    for (int i = 0; i < 4; i++) ldsm4t(line + (((2 * i) ^ x) << 4), a[i]);
}
__device__ __forceinline__ void pick2(const float (&c)[4][4], int tig, float& v0, float& v1) {
    v0 = (tig & 2) ? ((tig & 1) ? c[3][0] : c[2][0]) : ((tig & 1) ? c[1][0] : c[0][0]);
    v1 = (tig & 2) ? ((tig & 1) ? c[3][2] : c[2][2]) : ((tig & 1) ? c[1][2] : c[0][2]);
}

__device__ __forceinline__ int col8(int lane) { return 4 * (lane & 1) + (lane & 2) + ((lane >> 2) & 1); }
__device__ __forceinline__ float warp_cols(float a, float b, float c, float d, int lane) {
    const bool p = lane & 2, q = lane & 4;
    const float k0 = (p ? c : a) + __shfl_xor_sync(0xffffffffu, p ? a : c, 2);
    const float k1 = (p ? d : b) + __shfl_xor_sync(0xffffffffu, p ? b : d, 2);
    float k = (q ? k1 : k0) + __shfl_xor_sync(0xffffffffu, q ? k0 : k1, 4);
    k += __shfl_xor_sync(0xffffffffu, k, 8);
    return k + __shfl_xor_sync(0xffffffffu, k, 16);
}

__device__ __forceinline__ uint32_t* mbox(int b, uint32_t side) {
    const uintptr_t base = (reinterpret_cast<uintptr_t>(g_boxes) + 8191) & ~(uintptr_t)8191;
    return reinterpret_cast<uint32_t*>(base) + (2 * b + (side & 1u)) * 1024;
}
__device__ __forceinline__ int group_begin(int q) { return (NSTATIC * q) / NG; }
__device__ __forceinline__ void prefetch_map(const CUtensorMap* m) { asm volatile("prefetch.tensormap [%0];" ::"l"(m) : "memory"); }

struct Ptrs { const __nv_bfloat16 *pf, *x, *c; __nv_bfloat16* out; };

__global__ void __launch_bounds__(NTHREADS, 1)
fused_kernel(const __grid_constant__ Ptrs ptr, const __grid_constant__ Maps maps) {
    extern __shared__ __align__(1024) unsigned char smem[];
    asm volatile("{\n.reg .pred p;\n.reg .u32 t;\n.reg .u64 a;\nmov.u32 t, %%ctaid.x;\nmad.wide.u32 a, t, %1, %0;\nmov.u32 t, %%tid.x;\n"
                 "setp.eq.u32 p, t, 0;\n@p cp.async.bulk.prefetch.L2.global [a], %1;\n}" ::"l"(ptr.pf), "n"(PF_BYTES) : "memory");
    const uint32_t sb = (uint32_t)__cvta_generic_to_shared(smem);
    const int tid = threadIdx.x, warp = tid >> 5, lane = tid & 31, cta = blockIdx.x;
    const uint32_t bars = sb + OFF_BAR;
    volatile int* ntot = reinterpret_cast<volatile int*>(smem + OFF_NTOT);
    const bool has_mod = cta >= MOD_C0, has_q = cta < NQ;
    const bool stat_wo = cta < C_X, extra = cta >= C_X && cta < C_P, pool_head = cta >= C_P && cta < C_E;

    const int g0 = group_begin(cta / GRP), t0 = g0 + cta % GRP, t1 = group_begin(cta / GRP + 1);
    uint32_t xp = 0, cp = 0, epoch = 0;
    uint64_t pol = 0;
#define ISSUE_SLICE(i, map, off, bar, col)                                  \
    do {                                                                    \
        tma2d(sb + (off) + 8192 * (i), (map), (col), 128 * (i), (bar), pol); \
        if ((i) < 4) tma2d(sb + (off) + 8192 * (i) + 4096, (map), (col), 128 * (i) + 64, (bar), pol); \
    } while (0)
    if (tid == 0) {
        const CUtensorMap* m0 = has_mod ? &maps.wmod : &maps.wq;
        prefetch_map(m0);
        const uint32_t b0 = bars + 8 * (has_mod ? B_WMOD : B_WQ), off = has_mod ? OFF_WMOD : OFF_WQ;
        const int col = 32 * (has_mod ? cta - MOD_C0 : cta);
#pragma unroll
        for (int i = 0; i < 5; i++) mbar_init(b0 + 8 * i, 1);
        asm volatile("fence.proxy.async.shared::cta;" ::: "memory");
        asm volatile("createpolicy.fractional.L2::evict_first.b64 %0, 1.0;" : "=l"(pol));
#pragma unroll
        for (int i = 0; i < 5; i++) {
            mbar_expect(b0 + 8 * i, i < 4 ? 8192 : 4096);
            ISSUE_SLICE(i, m0, off, b0 + 8 * i, col);
        }
    }
    __syncwarp();
    if (tid == 32 * W_RED) {
#pragma unroll
        for (int b = 0; b < 27; b++) mbar_init(bars + 8 * b, 1);
        asm volatile("fence.proxy.async.shared::cta;" ::: "memory");
    } else if (tid == 32 * W_PROD) {
        prefetch_map(&maps.wq);
        prefetch_map(&maps.k);
        prefetch_map(&maps.v);
        if (has_mod) {
#pragma unroll
            for (int b = B_WQ; b < B_END; b++) mbar_init(bars + 8 * b, 1);
        }
        asm volatile("fence.proxy.async.shared::cta;" ::: "memory");
        asm volatile("createpolicy.fractional.L2::evict_first.b64 %0, 1.0;" : "=l"(pol));
    } else if (tid == 32 * W_RED + 32) {
#pragma unroll
        for (int b = 27; b < B_WMOD; b++) mbar_init(bars + 8 * b, b >= B_DOWN && b < B_SDONE ? 2 : 1);
        asm volatile("fence.proxy.async.shared::cta;" ::: "memory");
        *ntot = 0x7fffffff;
    } else if (warp < NCW) {
        asm volatile("ld.global.nc.u32 %0, [%1];" : "=r"(cp) : "l"(ptr.c + 2 * tid));
        asm volatile("ld.global.nc.u32 %0, [%1];" : "=r"(xp) : "l"(ptr.x + 2 * tid));
        if (warp == 0) {
            if (has_mod) stg1(g_mod + 32 * (cta - MOD_C0) + lane, 0);
            if (has_q) stg1(g_q + 32 * cta + lane, 0);
        }
    }
    __syncwarp();
    if (warp != W_PROD) asm volatile("ld.relaxed.gpu.global.u32 %0, [%1];" : "=r"(epoch) : "l"(&g_epoch) : "memory");
    __syncthreads();

    const int head0 = g0 / TPH;
    const int last_seg = t1 > (head0 + 1) * TPH;
    const int n0 = (min(t1, (head0 + 1) * TPH) - t0 + GRP - 1) / GRP;
    const int n01 = (t1 - t0 + GRP - 1) / GRP;
    const int woff = (-n01) & (NAS - 1);

    if (warp == W_PROD) {
        if (lane == 0) {
            if (sb & 1023) __trap();
            const uint32_t c_start = clk();
            uint32_t hist[DMAX];
#pragma unroll
            for (int i = 0; i < DMAX; i++) hist[i] = bars + 8 * ((has_mod ? B_WMOD : B_WQ) + max(4 - i, 0));
#define WAIT_LANDED(D) mbar_wait(hist[(D) - 1] & ~1u, hist[(D) - 1] & 1u)
#define PUSH_ITEM(bar, par)                                                 \
            do {                                                            \
                _Pragma("unroll") for (int i_ = DMAX - 1; i_ > 0; i_--) hist[i_] = hist[i_ - 1]; \
                hist[0] = (bar) | (par);                                    \
            } while (0)
            uint32_t phm = 0;
#define ISSUE_TILE(D, i)                                                    \
            do {                                                            \
                const int w_ = ((i) + woff) & (NAS - 1);                    \
                const uint32_t ph_ = (phm >> w_) & 1u;                      \
                const uint32_t fb_ = bars + 16 * w_, dst_ = sb + OFF_SLOT0 + ((w_ + NAS - NAP) & (NAS - 1)) * (2 * ITEM); \
                phm ^= 1u << w_;                                            \
                _Pragma("unroll") for (int kv_ = 0; kv_ < 2; kv_++) {       \
                    mbar_wait(fb_ + 8 * (B_EMPTY + kv_), ph_ ^ 1);          \
                    mbar_expect(fb_ + 8 * kv_, ITEM);                       \
                    WAIT_LANDED(D);                                         \
                    tma2d(dst_ + kv_ * ITEM, kv_ ? &maps.v : &maps.k, 0, (t0 + GRP * (i)) * (2 * TILE), fb_ + 8 * kv_, pol); \
                    PUSH_ITEM(fb_ + 8 * kv_, ph_);                          \
                }                                                           \
            } while (0)

            if (has_mod && has_q) {
#pragma unroll 1
                for (int i = 0; i < 5; i++) {
                    const uint32_t bar = bars + 8 * (B_WQ + i);
                    mbar_expect(bar, i < 4 ? 8192 : 4096);
                    WAIT_LANDED(D_PRO);
                    ISSUE_SLICE(i, &maps.wq, OFF_WQ, bar, 32 * cta);
                    PUSH_ITEM(bar, 0u);
                }
            }
#pragma unroll 1
            for (int i = 0; i < N_PRO; i++) {
                if (i == NAS) {
#pragma unroll
                    for (int k = 0; k < D_PRO; k++) {
                        bool free;
                        uint32_t n = 0;
                        while (!(free = mbar_test(bars + 16 * woff + 8 * B_EMPTY, 0)) && !mbar_test(hist[D_PRO - 1 - k], 0)) spin_guard(n);
                        if (free) break;
                        asm volatile("cp.async.bulk.prefetch.tensor.2d.L2.global.L2::cache_hint [%0, {0, %1}], %2;"
                                     ::"l"((k & 1) ? &maps.v : &maps.k), "r"((t0 + GRP * (NAS + k / 2)) * (2 * TILE)), "l"(pol) : "memory");
                    }
                }
                ISSUE_TILE(D_PRO, i);
            }
#pragma unroll 1
            for (int i = N_PRO; i < n01; i++) ISSUE_TILE(D_MAIN, i);

            prefetch_map(&maps.wo); prefetch_map(&maps.gate); prefetch_map(&maps.up); prefetch_map(&maps.down);
            if (extra) { prefetch_map(&maps.gatex); prefetch_map(&maps.upx); }
            if (cta < NRED) prefetch_map(&maps.gb);
            if (pool_head) {
#pragma unroll 1
                for (int i = 0; i < 4; i++) {
                    const uint32_t bar = bars + 8 * (B_WO + i);
                    mbar_expect(bar, 9216);
                    WAIT_LANDED(D_POOL);
                    tma2d(sb + OFF_WO + 9216 * i, &maps.wo, 0, 9 * (32 * cta + 8 * i), bar, pol);
                    PUSH_ITEM(bar, 0u);
                }
            }
            mbar_wait(bars + 8 * B_SEL, 0);
            uint32_t c_tk = 0, left = 0;
            int n = 0, w = 0;
#pragma unroll 1
            while (true) {
                const uint32_t ph = (phm >> w) & 1u, fb = bars + 16 * w, dst = sb + OFF_RING + w * (2 * ITEM);
                WAIT_LANDED(D_POOL);
                const uint32_t tk = atomicAdd(g_ticket, 1u);
                mbar_wait(fb + 8 * (B_EMPTY + 1), ph ^ 1);
                if (tk >= (uint32_t)NPOOL) break;
                mbar_expect(fb, ITEM);
                tma2d(dst, &maps.k, 0, (NSTATIC + (int)tk) * (2 * TILE), fb, pol);
                mbar_expect(fb + 8, ITEM);
                tma2d(dst + ITEM, &maps.v, 0, (NSTATIC + (int)tk) * (2 * TILE), fb + 8, pol);
                c_tk = clk();
                left = NPOOL - tk;
                PUSH_ITEM(fb, ph);
                PUSH_ITEM(fb + 8, ph);
                phm ^= 1u << w;
                n++;
                if (++w == NAP) w = 0;
            }
            *ntot = n;

            uint32_t due = clk();
            const float cpm = (float)(due - c_start) * (1.0f / 540.0f);
            if (n) { const uint32_t dry = c_tk + (uint32_t)(cpm * (2 * ITEM * 1e-6f) * left); if ((int)(due - dry) > 0) due = dry; }
            due += (uint32_t)(cpm * T_LEAD);
#define WAIT_DUE(step)                                                      \
            do {                                                            \
                WAIT_LANDED(D_CAP);                                         \
                while ((int)(clk() - due) < 0) {}                           \
                due += (step);                                              \
            } while (0)
            uint32_t step = (uint32_t)(cpm * (C_X * 9216e-6f));
            if (stat_wo) {
#pragma unroll 1
                for (int i = 0; i < 5; i++) {
                    const uint32_t bar = bars + 8 * (B_WO + i);
                    mbar_expect(bar, 9216);
                    WAIT_DUE(step);
                    tma2d(sb + OFF_WO + 9216 * i, &maps.wo, 0, 9 * (40 * cta + 8 * i), bar, pol);
                    PUSH_ITEM(bar, 0u);
                }
            } else {
                due += 5 * step;
            }
            mbar_wait(bars + 8 * B_SDONE, 0);
            step = (uint32_t)(cpm * (64 * FF * 4e-6f));
            const int xcol = FX0 + 16 * (cta - C_X);
#pragma unroll 1
            for (int i = 0; i < 9; i++) {
                const uint32_t bar = bars + 8 * (B_GU + i);
                mbar_expect(bar, extra ? 12288 : 8192);
                WAIT_DUE(step);
                tma2d(sb + OFF_GATE + 4096 * i, &maps.gate, 32 * cta, 64 * i, bar, pol);
                tma2d(sb + OFF_UP + 4096 * i, &maps.up, 32 * cta, 64 * i, bar, pol);
                if (extra) {
                    tma2d(sb + OFF_GATEX + 2048 * i, &maps.gatex, xcol, 64 * i, bar, pol);
                    tma2d(sb + OFF_UPX + 2048 * i, &maps.upx, xcol, 64 * i, bar, pol);
                }
                PUSH_ITEM(bar, 0u);
            }
            mbar_wait(bars + 8 * B_PDONE, 0);
            step = (uint32_t)(cpm * (FF * 1152e-6f / 4) * (extra ? 0.6f : 1.0f));
#pragma unroll 1
            for (int i = 0; i < (extra ? 6 : 4); i++) {
                const uint32_t bar = bars + 8 * (B_DOWN + (i >> 1));
                mbar_expect(bar, 9216);
                WAIT_DUE(step);
                tma2d(sb + OFF_DOWN + 9216 * i, &maps.down, 0, 9 * (i < 4 ? 32 * cta + 8 * i : xcol + 8 * (i - 4)), bar, pol);
                PUSH_ITEM(bar, 0u);
            }
            if (cta < NRED) {
                const uint32_t bar = bars + 8 * B_GB;
                mbar_expect(bar, DM * 16);
                due += (uint32_t)(cpm * T_GB);
                WAIT_DUE(0);
#pragma unroll
                for (int i = 0; i < 3; i++) tma2d(sb + OFF_GB + 3072 * i, &maps.gb, 5 * DM + 8 * cta, 192 * i, bar, pol);
            }
        }
        return;
    }

    const uint32_t tag = epoch >= 3u ? 1u : epoch + 1u;

    if (warp >= W_RED) {
        const int half = warp - W_RED, col = 8 * cta + col8(lane);
        uint32_t* vec = reinterpret_cast<uint32_t*>(smem + OFF_VEC);
        uint32_t* sel = reinterpret_cast<uint32_t*>(smem + OFF_SEL);
        {
            const int nb = cta < NRED ? 2 : pool_head ? 5 : 0, b0 = cta < NRED ? 2 * cta : BOX_P + 5 * (cta - C_P);
            bar_sync(3, 32 * (NCW + 2));
            uint32_t* const pw = mbox(lane < nb ? b0 + lane : BOX_X + (cta & 3), half) + DM + 8 * ((cta >> 2) & 7);
            if (lane <= nb) {
#pragma unroll 1
                for (int j = 0; j < 7; j++) { stg4(pw + 64 * j, 0, 0, 0, 0); stg4(pw + 64 * j + 4, 0, 0, 0, 0); }
            }
            uint32_t best = ~0u;
#pragma unroll 1
            for (int r = 0; r < NPROBE * (nb + 1); r++) {
                if (lane == r % (nb + 1)) {
                    uint32_t* const q = pw + 64 * (r % 7);
                    const uint32_t c0 = clk();
                    uint32_t v, c1;
                    asm volatile("atom.relaxed.gpu.global.add.u32 %0, [%1], 4;" : "=r"(v) : "l"(q) : "memory");
                    asm volatile("{\n.reg .pred p;\nsetp.eq.u32 p, %1, 0xffffffff;\n@p trap;\nmov.u32 %0, %%clock;\n}" : "=r"(c1) : "r"(v) : "memory");
                    best = min(best, c1 - c0);
                }
                __syncwarp();
            }
            if (lane < 8) sel[80 + 8 * half + lane] = best;
            bar_sync(5, 64);
            const uint32_t sides = __ballot_sync(0xffffffffu, lane <= nb && sel[88 + (lane & 7)] < sel[80 + (lane & 7)]);
            for (int b = 0; b < nb; b++) {
                uint32_t* q = mbox(b0 + b, sides >> b) + 4 * (32 * half + lane);
#pragma unroll
                for (int i = 0; i < 4; i++) stg4(q + 256 * i, 0, 0, 0, 0);
            }
            if (cta == 0 && half && lane < 2) stg4(g_ticket + 4 * lane, 0, 0, 0, 0);
            __threadfence();
            bar_sync(5, 64);
            if (!half && lane == 0) {
                if (nb) stg1(g_sel + (cta < NRED ? cta : NRED + cta - C_P), (sides << 2) | tag);
                sel[80] = sides >> nb;
            }
            for (int i = 32 * half + lane; i < NRED + 8; i += 64) {
                uint32_t v, n = 0;
                do { __nanosleep(4000); v = ldg1(g_sel + i); spin_guard(n); } while ((v ^ tag) & 3u);
                sel[i] = v >> 2;
            }
            __threadfence();
            if (!half && lane == 0) mbar_arrive(bars + 8 * B_SEL);
        }
        bar_sync(3, 32 * (NCW + 2));
        float x1 = 0.f;
        if (cta < NRED) {
            uint32_t* const xs = mbox(BOX_X + (lane >> 3), 0) + col;
            const float x0 = __bfloat162float(ptr.x[col]);
            uint32_t ga, n = 0, bad;
            do { ga = ldg1(g_mod + 2 * DM + col); spin_guard(n); } while ((ga ^ tag) & 3u);
            const int t = 32 * half + lane;
            const uint32_t* src = mbox(2 * cta, sel[cta]) + 4 * t;
            uint4 v[4];
#pragma unroll
            for (int i = 0; i < 4; i++) {
                const uint32_t w = 64 * i + t < 2 * NY ? 0 : tag;
                v[i] = make_uint4(w, w, w, w);
            }
            mbar_wait(bars + 8 * B_GU, 0);
            do {
#pragma unroll
                for (int i = 0; i < 4; i++) if (bad4(v[i], tag)) v[i] = ldg4(src + 256 * i);
                bad = bad4(v[0], tag) | bad4(v[1], tag) | bad4(v[2], tag) | bad4(v[3], tag);
                spin_guard(n);
            } while (bad);
            __syncwarp();
#define SUM4(f) ((untag(v[0].f) + untag(v[1].f)) + (untag(v[2].f) + untag(v[3].f)))
            const float k = warp_cols(SUM4(x), SUM4(y), SUM4(z), SUM4(w), lane);
#undef SUM4
            if (half) {
                if (lane < 8) vec[48 + lane] = __float_as_uint(k);
                asm volatile("bar.arrive 5, 64;" ::: "memory");
            } else {
                bar_sync(5, 64);
                x1 = rbf(x0 + rbf(untag(ga) * rbf(k + __uint_as_float(vec[48 + (lane & 7)]))));
                stg1(xs, __float_as_uint(x1) | tag);
                stg1(xs + 1024, __float_as_uint(x1) | tag);
                if (cta == 0 && lane == 0) g_epoch = tag;
            }
        }
        {
            const int pr = 12 * half + min(lane & 15, 11);
            const float* q = reinterpret_cast<const float*>(smem + OFF_RED) + 720 + 2 * pr + 48 * (lane >> 4);
            bar_sync(4, 32 * (NCW + 2));
            float2 v[NCW];
#pragma unroll
            for (int w = 0; w < NCW; w++) v[w] = *reinterpret_cast<const float2*>(q + 96 * w);
#define SUM9(f) ((((v[0].f + v[1].f) + (v[2].f + v[3].f)) + ((v[4].f + v[5].f) + (v[6].f + v[7].f))) + v[8].f)
            const uint32_t a = pack2(SUM9(x), SUM9(y)), b = __shfl_xor_sync(0xffffffffu, a, 16);
#undef SUM9
            if (lane < 12) vec[24 + pr] = pack2(blo(a) * blo(b), bhi(a) * bhi(b));
            asm volatile("bar.arrive 8, %0;" ::"n"(32 * (NCW + 2)) : "memory");
        }
        if (cta >= NRED) return;
        float* red = reinterpret_cast<float*>(smem + OFF_RED);
        {
            const int g = lane >> 2, tig = lane & 3;
            const uint32_t* sv = reinterpret_cast<const uint32_t*>(smem + OFF_SILU) + 144 * half + (g & 4) + tig;
            uint32_t bb[9][2];
#pragma unroll
            for (int t = 0; t < 9; t++) { bb[t][0] = sv[16 * t]; bb[t][1] = sv[16 * t + 8]; }
            mbar_wait(bars + 8 * B_GB, 0);
            float c[3][4] = {};
#pragma unroll
            for (int t = 0; t < 9; t++) {
                uint32_t a[4];
                ldsm4t(sb + OFF_GB + (288 * half + 32 * t + lane) * 16, a);
                mma16816(c[t % 3], a, bb[t][0], bb[t][1]);
            }
            if (!(tig & 1)) red[96 + 4 * g + 2 * half + (tig >> 1)] = tig ? c[0][2] + c[1][2] + c[2][2] : c[0][0] + c[1][0] + c[2][0];
        }
        if (half) {
            asm volatile("bar.arrive 6, %0;" ::"n"(32 * (NCW + 2)) : "memory");
        } else {
            const float* q = red + 12 * (lane & 7);
            bar_sync(6, 32 * (NCW + 2));
            const float4 a = *reinterpret_cast<const float4*>(q), b = *reinterpret_cast<const float4*>(q + 4);
            const float d = rbf((((a.x + a.y) + (a.z + a.w)) + ((b.x + b.y) + (b.z + b.w))) + q[8]);
            const float4 e = *reinterpret_cast<const float4*>(red + 96 + 4 * col8(lane));
            const float gb = rbf((e.x + e.y) + (e.z + e.w));
            if (lane < 8) ptr.out[col] = __float2bfloat16_rn(x1 + rbf(gb * d));
        }
        return;
    }

    float* red = reinterpret_cast<float*>(smem + OFF_RED);
    float* stat = reinterpret_cast<float*>(smem + OFF_STAT);
    const int g = lane >> 2, tig = lane & 3;
    uint32_t cb1 = 0, sbp = 0;
    {
        const float xa = blo(xp), xb = bhi(xp);
        ln_stats_part(xa, xb, stat, warp, lane);
        const float ca = blo(cp), cb = bhi(cp);
        cp = pack2(ca * rcp(1.0f + ex2(-1.4426950408889634f * ca)), cb * rcp(1.0f + ex2(-1.4426950408889634f * cb)));
        reinterpret_cast<uint32_t*>(smem + OFF_SILU)[tid] = cp;
        if (has_mod) {
            mbar_wait(bars + 8 * (B_WMOD + (warp >> 1)), 0);
            gemv32(sb + OFF_WMOD + 4096 * warp, cp, red + 80 * warp, lane);
        }
        bar_sync(2, 32 * NCW);
        if (has_mod && warp == 0) red1(g_mod + 32 * (cta - MOD_C0) + lane, __float_as_uint(rbf(sum9(red + lane))) | tag);
        if (has_q) {
            float mean, rsd;
            ln_stats_fin(stat, mean, rsd);
            mbar_wait(bars + 8 * (B_WQ + (warp >> 1)), 0);
            uint2 sa, sc;
            uint32_t n = 0;
            do { sa = ldg2(g_mod + 2 * tid); sc = ldg2(g_mod + DM + 2 * tid); spin_guard(n); } while (bad2(sa, tag) | bad2(sc, tag));
            const uint32_t hp = ln_apply(xa, xb, mean, rsd, pack2(1.0f + untag(sc.x), 1.0f + untag(sc.y)), __byte_perm(sa.x, sa.y, 0x7632));
            __syncwarp();
            gemv32(sb + OFF_WQ + 4096 * warp, hp, red + 720 + 80 * warp, lane);
            bar_sync(2, 32 * NCW);
            if (warp == 0) red1(g_q + 32 * cta + lane, __float_as_uint(rbf(sum9(red + 720 + lane))) | tag);
        }
        {
            uint4 v = make_uint4(tag, tag, tag, tag);
            uint2 s2 = make_uint2(0, 0), c2 = s2;
            uint32_t n = 0;
            do {
                if (tid < 64) v = ldg4(g_q + 256 * head0 + 4 * tid);
                if (bad2(s2, tag) | bad2(c2, tag)) { s2 = ldg2(g_mod + 3 * DM + 2 * tid); c2 = ldg2(g_mod + 4 * DM + 2 * tid); }
                spin_guard(n);
            } while (bad4(v, tag) | bad2(s2, tag) | bad2(c2, tag));
            if (tid < 64)
                *reinterpret_cast<uint2*>(smem + OFF_Q + 8 * tid) = make_uint2(__byte_perm(v.x, v.y, 0x7632), __byte_perm(v.z, v.w, 0x7632));
            sbp = __byte_perm(s2.x, s2.y, 0x7632);
            cb1 = pack2(1.0f + untag(c2.x), 1.0f + untag(c2.y));
        }
        bar_sync(3, 32 * (NCW + 2));
    }
    const uint32_t* sel = reinterpret_cast<const uint32_t*>(smem + OFF_SEL);

    if (warp < NAS) {
        const int r = lane & 7, var = r >> 2;
        const uint32_t kofs = (r + 8 * ((lane >> 3) & 1)) * 256, kx = (lane >> 4) ^ var ^ (2 * (r & 3));
        const uint32_t vofs = (r + 8 * (lane >> 4)) * 256, vx = ((lane >> 3) & 1) ^ var ^ (2 * (r & 3));
        const bool valid = tig == (g >> 2);
        float* stage = reinterpret_cast<float*>(smem + OFF_STAGE);
        const uint32_t slot = sb + OFF_SLOT0 + ((warp + NAS - NAP) & (NAS - 1)) * (2 * ITEM);
        const uint32_t kb = slot + kofs, vb = slot + ITEM + vofs;
        const uint32_t kfull = bars + 16 * warp, kempty = kfull + 8 * B_EMPTY;
        int i = (warp - woff) & (NAS - 1);
        uint32_t ph = 0;
#pragma unroll 1
        for (int seg = 0; seg < 3; seg++) {
            if (seg == 1 && !last_seg) continue;
            if (seg == 2) {
                if (warp >= NAP) break;
                i = warp;
            }
            uint32_t qf[8][2];
            {
                if (seg) mbar_wait(bars + 8 * B_Q2, 0);
                const uint32_t* qs = reinterpret_cast<const uint32_t*>(smem + OFF_Q) + 128 * seg + 64 * (g & 1) + tig;
                const int qv = (g >> 1) & 1;
#pragma unroll
                for (int s = 0; s < 8; s++) { qf[s][0] = qs[8 * s + 4 * qv]; qf[s][1] = qs[8 * s + 4 * (qv ^ 1)]; }
            }
            float o[8][4] = {};
            float m0 = NEG_BIG, m1 = NEG_BIG, l0 = 0.f, l1 = 0.f;
            const int end = seg == 0 ? n0 : n01;
            const int nw = seg == 2 ? NAP : NAS;
#pragma unroll 1
            for (;; i += nw) {
                if (seg < 2) {
                    if (i >= end) break;
                    mbar_wait(kfull, ph);
                } else {
                    bool stop = false;
                    uint32_t n = 0;
                    while (true) {
                        if (i >= *ntot) { stop = true; break; }
                        if (mbar_test(kfull, ph)) break;
                        spin_guard(n);
                    }
                    if (__any_sync(0xffffffffu, stop)) break;
                }
                float s[2][2][4] = {};
#pragma unroll
                for (int st = 0; st < 8; st++) {
#pragma unroll
                    for (int mt = 0; mt < 2; mt++) {
                        uint32_t a[4];
                        ldsm4(kb + mt * 4096 + (st >> 2) * 128 + (((2 * (st & 3)) ^ (st >> 2) ^ kx) << 4), a);
                        mma16816(s[mt][st & 1], a, qf[st][0], qf[st][1]);
                    }
                }
                __syncwarp();
                if (lane == 0) mbar_arrive(kempty);
                float t[2][4];
#pragma unroll
                for (int mt = 0; mt < 2; mt++)
#pragma unroll
                    for (int j = 0; j < 4; j += 2) {
                        uint32_t p = pack2(s[mt][0][j] + s[mt][1][j], s[mt][0][j + 1] + s[mt][1][j + 1]);
                        p = pack2(blo(p) * 0.08838834764831845f, bhi(p) * 0.08838834764831845f);
                        if (!valid) p = 0xff80ff80u;
                        t[mt][j] = blo(p) * 1.4426950408889634f;
                        t[mt][j + 1] = bhi(p) * 1.4426950408889634f;
                    }
                float x0 = fmaxf(fmaxf(t[0][0], t[0][2]), fmaxf(t[1][0], t[1][2]));
                float x1 = fmaxf(fmaxf(t[0][1], t[0][3]), fmaxf(t[1][1], t[1][3]));
                if (__any_sync(0xffffffffu, x0 > m0 || x1 > m1)) {
#pragma unroll
                    for (int d = 16; d; d >>= 1) {
                        x0 = fmaxf(x0, __shfl_xor_sync(0xffffffffu, x0, d));
                        x1 = fmaxf(x1, __shfl_xor_sync(0xffffffffu, x1, d));
                    }
                    x0 = fmaxf(x0, m0); x1 = fmaxf(x1, m1);
                    const float a0 = ex2(m0 - x0), a1 = ex2(m1 - x1);
                    m0 = x0; m1 = x1;
                    l0 *= a0; l1 *= a1;
#pragma unroll
                    for (int j = 0; j < 8; j++) { o[j][0] *= a0; o[j][1] *= a1; o[j][2] *= a0; o[j][3] *= a1; }
                }
                uint32_t pb[2][2];
#pragma unroll
                for (int mt = 0; mt < 2; mt++) {
                    const float p0 = ex2(t[mt][0] - m0), p1 = ex2(t[mt][1] - m1), p2 = ex2(t[mt][2] - m0), p3 = ex2(t[mt][3] - m1);
                    l0 += p0 + p2; l1 += p1 + p3;
                    pb[mt][0] = movmat(pack2(p0, p1));
                    pb[mt][1] = movmat(pack2(p2, p3));
                }
                mbar_wait(kfull + 8, ph);
#pragma unroll
                for (int mt = 0; mt < 2; mt++) {
#pragma unroll
                    for (int j = 0; j < 8; j++) {
                        uint32_t a[4];
                        ldsm4t(vb + mt * 4096 + (j >> 2) * 128 + (((2 * (j & 3)) ^ (j >> 2) ^ vx) << 4), a);
                        mma16816(o[j], a, pb[mt][0], pb[mt][1]);
                    }
                }
                __syncwarp();
                if (lane == 0) mbar_arrive(kempty + 8);
                ph ^= 1;
            }
            l0 += __shfl_xor_sync(0xffffffffu, l0, 17); l1 += __shfl_xor_sync(0xffffffffu, l1, 17);
            float* sw = stage + 260 * warp;
#pragma unroll
            for (int j = 0; j < 8; j++) {
                const float u0 = o[j][0] + __shfl_xor_sync(0xffffffffu, o[j][2], 1);
                const float u1 = o[j][1] + __shfl_xor_sync(0xffffffffu, o[j][3], 1);
                if (tig < 2) { sw[16 * j + 8 * tig + g] = u0; sw[128 + 16 * j + 8 * tig + g] = u1; }
                if (j == 2 || j == 5) {
                    l0 += __shfl_xor_sync(0xffffffffu, l0, j == 2 ? 4 : 8);
                    l1 += __shfl_xor_sync(0xffffffffu, l1, j == 2 ? 4 : 8);
                }
            }
            if (lane == 0) *reinterpret_cast<float4*>(sw + 256) = make_float4(m0, l0, m1, l1);
            bar_sync(1, 32 * nw);
            if (tid == 128 && seg >= last_seg) mbar_arrive(bars + 8 * (seg == 2 ? B_PDONE : B_SDONE));
            if (tid < 128) {
                const int h = tid >> 6;
                float2 ml[NAS], ov[NAS];
                float M = NEG_BIG;
#pragma unroll
                for (int w = 0; w < NAS; w++) {
                    ml[w] = make_float2(NEG_BIG, 0.f); ov[w] = make_float2(0.f, 0.f);
                    if (w < NAP || seg < 2) {
                        ml[w] = *reinterpret_cast<const float2*>(stage + 260 * w + 256 + 2 * h);
                        ov[w] = *reinterpret_cast<const float2*>(stage + 260 * w + 2 * tid);
                    }
                    M = fmaxf(M, ml[w].x);
                }
                float a = 0.f, b = 0.f, L = 0.f;
#pragma unroll
                for (int w = 0; w < NAS; w++) {
                    const float e = ex2(ml[w].x - M);
                    a += e * ov[w].x; b += e * ov[w].y; L += e * ml[w].y;
                }
                const uint32_t w0 = tagw(M, tag), w1 = (__float_as_uint(M) << 2) | tag, w2 = tagw(L, tag);
                if (seg == 2) {
                    const int p = tid >> 4, k = cta / 28;
                    uint32_t* q = mbox(BOX_P + 5 * p + k, sel[NRED + p] >> k);
                    stg2(q + 32 * (cta % 28) + 2 * (tid & 15), tagw(a, tag), tagw(b, tag));
                    if ((tid & 15) == 0) stg4(q + 896 + 4 * (cta % 28), w0, w1, w2, w2);
                } else {
                    stg2(g_part + (cta * 2 + seg) * 256 + 2 * tid, tagw(a, tag), tagw(b, tag));
                    if ((tid & 63) == 0) stg4(g_ml + ((seg * 2 + h) * 144 + cta) * 4, w0, w1, w2, w2);
                }
            }
            if (seg < 2) { if (seg == last_seg) bar_sync(3, 32 * (NCW + 2)); else bar_sync(1, 32 * NAS); }
        }
    } else {
#pragma unroll 1
        for (int k = 0; k < 4; k++) {
            uint4 v;
            uint32_t n = 0;
            do {
                __nanosleep(1000);
                v = ldg4(g_q + 256 * (k < 2 ? head0 + 1 : HKV - 1) + 128 * (k & 1) + 4 * lane);
                spin_guard(n);
            } while (bad4(v, tag));
            *reinterpret_cast<uint2*>(smem + OFF_Q + 512 + 256 * k + 8 * lane) =
                make_uint2(__byte_perm(v.x, v.y, 0x7632), __byte_perm(v.z, v.w, 0x7632));
        }
        __syncwarp();
        if (lane == 0) mbar_arrive(bars + 8 * B_Q2);
        bar_sync(3, 32 * (NCW + 2));
    }
    const int r0 = 8 * warp + 2 * tig;
    const uint32_t sel0 = sel[r0], sel1 = sel[r0 + 1];
#define PUBLISH_Y(j)                                                        \
    do {                                                                    \
        stg1(mbox(2 * r0, sel0) + 8 * (j) + g, tagw(v0, tag));               \
        stg1(mbox(2 * r0 + 2, sel1) + 8 * (j) + g, tagw(v1, tag));           \
    } while (0)

    uint32_t* vec = reinterpret_cast<uint32_t*>(smem + OFF_VEC);
    if (stat_wo) {
        const int u = tid - 32 * NAP;
        if (u >= 0 && u < 40) {
            const int row = 40 * cta + u, kvh = row >> 8, h = (row >> 7) & 1;
            int q = (kvh * TPH * NG) / NSTATIC;
            while (group_begin(q + 1) <= kvh * TPH) q++;
            while (group_begin(q) > kvh * TPH) q--;
            float M = NEG_BIG, num = 0.f, den = 0.f;
#pragma unroll 1
            for (; group_begin(q) < (kvh + 1) * TPH; q++) {
                const int seg = group_begin(q) / TPH == kvh ? 0 : 1;
                uint4 ml[GRP];
                uint32_t ov[GRP], bad, spin = 0;
                while (true) {
                    bad = 0;
#pragma unroll
                    for (int k = 0; k < GRP; k++) {
                        ov[k] = ldg1(g_part + ((GRP * q + k) * 2 + seg) * 256 + (row & 255));
                        ml[k] = ldg4(g_ml + ((seg * 2 + h) * 144 + GRP * q + k) * 4);
                    }
#pragma unroll
                    for (int k = 0; k < GRP; k++) bad |= bad4(ml[k], tag) | ((ov[k] ^ tag) & 3u);
                    if (!bad) break;
                    __nanosleep(300);
                    spin_guard(spin);
                }
#pragma unroll
                for (int k = 0; k < GRP; k++) {
                    const float m = __uint_as_float((ml[k].x & ~3u) | ((ml[k].y >> 2) & 3u)), Mn = fmaxf(M, m);
                    const float e0 = ex2(M - Mn), e1 = ex2(m - Mn);
                    num = num * e0 + e1 * untag(ov[k]);
                    den = den * e0 + e1 * untag(ml[k].z);
                    M = Mn;
                }
            }
            reinterpret_cast<uint16_t*>(vec)[u] = (uint16_t)pack2(num * rcp(den), 0.f);
        }
        bar_sync(2, 32 * NCW);
        float c[4][4] = {};
#pragma unroll
        for (int s = 0; s < 3; s++) {
            const uint32_t b0 = vec[8 * s + tig], b1 = s < 2 ? vec[8 * s + 4 + tig] : 0u;
            uint32_t a[4][4];
            mbar_wait(bars + 8 * (B_WO + 2 * s), 0);
            if (s < 2) mbar_wait(bars + 8 * (B_WO + 2 * s + 1), 0);
            load_frags64(sb + OFF_WO, s, s == 2, warp, lane, a);
#pragma unroll
            for (int i = 0; i < 4; i++) mma16816(c[i], a[i], b0, b1);
        }
        float v0, v1;
        pick2(c, tig, v0, v1);
        PUBLISH_Y(cta);
    } else if (pool_head) {
        uint32_t wa[2][4][4];
#pragma unroll
        for (int s = 0; s < 2; s++) {
            mbar_wait(bars + 8 * (B_WO + 2 * s), 0);
            mbar_wait(bars + 8 * (B_WO + 2 * s + 1), 0);
            load_frags64(sb + OFF_WO, s, false, warp, lane, wa[s]);
        }
        const int c0 = 16 * warp + (lane >> 3);
        const uint32_t* po[4];
        uint32_t mo[4];
#pragma unroll
        for (int k = 0; k < 4; k++) {
            const int c = min(c0 + 4 * k, NCTA - 1), b = c / 28, j = c % 28;
            po[k] = mbox(BOX_P + 5 * (cta - C_P) + b, sel[NRED + cta - C_P] >> b) + 32 * j + 4 * (lane & 7);
            mo[k] = 896 + 4 * j - 32 * j - 4 * (lane & 7);
        }
        if (warp >= NAP) mbar_wait(bars + 8 * B_PDONE, 0);
        uint4 ov[4], ml[4];
#pragma unroll
        for (int k = 0; k < 4; k++) {
            const uint32_t w = c0 + 4 * k < NCTA ? 0 : tag;
            ov[k] = make_uint4(w, w, w, w);
            ml[k] = make_uint4(tagw(NEG_BIG, tag), w, w, w);
        }
        uint32_t bad, spin = 0;
        do {
#pragma unroll
            for (int k = 0; k < 4; k++) {
                if (bad4(ov[k], tag)) ov[k] = ldg4(po[k]);
                if (bad4(ml[k], tag)) ml[k] = ldg4(po[k] + mo[k]);
            }
            bad = 0;
#pragma unroll
            for (int k = 0; k < 4; k++) bad |= bad4(ov[k], tag) | bad4(ml[k], tag);
            spin_guard(spin);
        } while (bad);
        __syncwarp();
        float mk[4];
#pragma unroll
        for (int k = 0; k < 4; k++) mk[k] = __uint_as_float((ml[k].x & ~3u) | ((ml[k].y >> 2) & 3u));
        float M = fmaxf(fmaxf(mk[0], mk[1]), fmaxf(mk[2], mk[3]));
        M = fmaxf(M, __shfl_xor_sync(0xffffffffu, M, 8));
        M = fmaxf(M, __shfl_xor_sync(0xffffffffu, M, 16));
        float a[5] = {};
#pragma unroll
        for (int k = 0; k < 4; k++) {
            const float e = ex2(mk[k] - M);
            a[0] += e * untag(ov[k].x); a[1] += e * untag(ov[k].y); a[2] += e * untag(ov[k].z); a[3] += e * untag(ov[k].w);
            a[4] += e * untag(ml[k].z);
        }
#pragma unroll
        for (int j = 0; j < 5; j++) a[j] += __shfl_xor_sync(0xffffffffu, a[j], 8);
#pragma unroll
        for (int j = 0; j < 5; j++) a[j] += __shfl_xor_sync(0xffffffffu, a[j], 16);
        if (lane < 8) *reinterpret_cast<float4*>(red + 40 * warp + 4 * lane) = make_float4(a[0], a[1], a[2], a[3]);
        if (lane == 0) *reinterpret_cast<float2*>(red + 40 * warp + 32) = make_float2(M, a[4]);
        if (warp < NCW - 1) {
            asm volatile("bar.arrive 7, %0;" ::"n"(32 * NCW) : "memory");
        } else {
            bar_sync(7, 32 * NCW);
            float2 sw[NCW];
            float ow[NCW], MM = NEG_BIG;
#pragma unroll
            for (int w = 0; w < NCW; w++) {
                sw[w] = *reinterpret_cast<const float2*>(red + 40 * w + 32);
                ow[w] = red[40 * w + lane];
                MM = fmaxf(MM, sw[w].x);
            }
            float num[2] = {}, den[2] = {};
#pragma unroll
            for (int w = 0; w < NCW; w++) { const float e = ex2(sw[w].x - MM); num[w & 1] += e * ow[w]; den[w & 1] += e * sw[w].y; }
            reinterpret_cast<uint16_t*>(vec)[lane] = (uint16_t)pack2((num[0] + num[1]) * rcp(den[0] + den[1]), 0.f);
        }
        bar_sync(2, 32 * NCW);
        float c[4][4] = {};
#pragma unroll
        for (int s = 0; s < 2; s++) {
            const uint32_t b0 = vec[8 * s + tig], b1 = vec[8 * s + 4 + tig];
#pragma unroll
            for (int i = 0; i < 4; i++) mma16816(c[i], wa[s][i], b0, b1);
        }
        float v0, v1;
        pick2(c, tig, v0, v1);
        PUBLISH_Y(cta - (C_P - C_X));
    }

    {
        uint32_t ga[4][6][4];
        const int r = lane & 7, mhi = (lane >> 3) & 1, khi = lane >> 4;
        const uint32_t box = sb + (mhi ? OFF_UP : OFF_GATE) + 4096 * warp + (8 * khi + r) * 64;
        const uint32_t boxx = sb + (mhi ? OFF_UPX : OFF_GATEX) + 2048 * warp + (8 * khi + r) * 32;
#define LOAD_GU()                                                           \
        do {                                                                \
            _Pragma("unroll") for (int s = 0; s < 4; s++)                   \
                _Pragma("unroll") for (int i = 0; i < 4; i++) ldsm4t(box + s * 1024 + ((i ^ (r >> 1)) << 4), ga[s][i]); \
            if (extra) {                                                    \
                _Pragma("unroll") for (int s = 0; s < 4; s++)               \
                    _Pragma("unroll") for (int i = 0; i < 2; i++) ldsm4t(boxx + s * 512 + ((i ^ (r >> 2)) << 4), ga[s][4 + i]); \
            }                                                               \
        } while (0)
        mbar_wait(bars + 8 * (B_GU + min(warp, X1_GATE)), 0);
        bool have = false;
        const uint32_t* px = mbox(BOX_X + (cta & 3), sel[80]) + 2 * tid;
        uint2 xv = make_uint2(0, 0);
        uint32_t n = 0;
        while (true) {
            if (!have && __all_sync(0xffffffffu, mbar_test(bars + 8 * (B_GU + warp), 0))) {
                have = true;
                LOAD_GU();
            }
            if (n == 0) mbar_wait(bars + 8 * (B_GU + X1_GATE), 0);
            if (bad2(xv, tag)) xv = ldg2(px);
            if (!__any_sync(0xffffffffu, bad2(xv, tag))) break;
            spin_guard(n);
        }
        const float xa = untag(xv.x), xb = untag(xv.y);
        ln_stats_part(xa, xb, stat + 20, warp, lane);
        bar_sync(2, 32 * NCW);
        float mean, rsd;
        ln_stats_fin(stat + 20, mean, rsd);
        const uint32_t hp = ln_apply(xa, xb, mean, rsd, cb1, sbp);
        if (!have) {
            mbar_wait(bars + 8 * (B_GU + warp), 0);
            LOAD_GU();
        }
        float c[6][4] = {};
        uint32_t b[4][2];
#pragma unroll
        for (int s = 0; s < 4; s++) {
            b[s][0] = __shfl_sync(0xffffffffu, hp, 8 * s + tig);
            b[s][1] = __shfl_sync(0xffffffffu, hp, 8 * s + 4 + tig);
#pragma unroll
            for (int i = 0; i < 4; i++) mma16816(c[i], ga[s][i], b[s][0], b[s][1]);
        }
        if (extra) {
#pragma unroll
            for (int s = 0; s < 4; s++)
#pragma unroll
                for (int i = 4; i < 6; i++) mma16816(c[i], ga[s][i], b[s][0], b[s][1]);
        }
        float* rw = red + 720 + 96 * warp + 48 * (tig & 1) + 8 * (tig >> 1) + g;
#pragma unroll
        for (int i = 0; i < 6; i += 2) {
            const float lo = (tig & 1) ? c[i][2] : c[i][0], hi = (tig & 1) ? c[i + 1][2] : c[i + 1][0];
            rw[8 * i] = (tig & 2) ? hi : lo;
        }
    }
    asm volatile("bar.arrive 4, %0;" ::"n"(32 * (NCW + 2)) : "memory");

    uint32_t da[3][4][4];
    const int zb = cta >= ZA, zo = 8 * (zb ? cta - ZA : NY + cta) + g;
    uint32_t* const z0 = mbox(2 * r0 + zb, sel0 >> zb) + zo;
    uint32_t* const z1 = mbox(2 * r0 + 2 + zb, sel1 >> zb) + zo;
    const int rb = tid >= 2 * ZA;
    const uint32_t* zr = mbox(2 * cta + rb, sel[min(cta, NRED - 1)] >> rb) + 4 * (rb ? tid - 2 * ZA : 2 * NY + tid);
    asm volatile("" : "+l"(zr));
    const uint32_t ok = __ballot_sync(0xffffffffu, lane < 3 && mbar_test(bars + 8 * (B_DOWN + min(lane, 2)), 0));
    const int nd = !(ok & 1u) ? 0 : !(ok & 2u) ? 1 : !(ok & 4u) ? 2 : 3;
    __syncwarp();
    uint32_t dadr[4];
    {
        const int row = 8 * (lane >> 4) + (lane & 7);
        const uint32_t line = sb + OFF_DOWN + (9 * row + warp) * 128, x = ((lane >> 3) & 1) ^ ((row + warp) & 7);
#pragma unroll
        for (int i = 0; i < 4; i++) { dadr[i] = line + (((2 * i) ^ x) << 4); asm volatile("" : "+r"(dadr[i])); }
    }
#define LOAD_DOWN(s) _Pragma("unroll") for (int i = 0; i < 4; i++) ldsm4t(dadr[i] + (s) * (16 * 1152), da[s][i])
#pragma unroll
    for (int s = 0; s < 3; s++) if (s < nd) { LOAD_DOWN(s); }
    bar_sync(8, 32 * (NCW + 2));
    {
        float c[4][4] = {};
#pragma unroll
        for (int s = 0; s < 3; s++) {
            if (s == 2 && !extra) break;
            const uint32_t b0 = vec[24 + 8 * s + tig], b1 = vec[24 + 8 * s + 4 + tig];
            if (s >= nd) {
                mbar_wait(bars + 8 * (B_DOWN + s), 0);
                LOAD_DOWN(s);
            }
#pragma unroll
            for (int i = 0; i < 4; i++) mma16816(c[i], da[s][i], b0, b1);
        }
        float v0, v1;
        pick2(c, tig, v0, v1);
        stg1(z0, tagw(v0, tag));
        stg1(z1, tagw(v1, tag));
    }
    if (cta < NRED) {
        uint4 v = make_uint4(tag, tag, tag, tag);
        if (tid < 2 * NCTA) {
            uint32_t n = 0;
            do { v = ldg4(zr); spin_guard(n); } while (bad4(v, tag));
        }
        __syncwarp();
        const float k = warp_cols(untag(v.x), untag(v.y), untag(v.z), untag(v.w), lane);
        if (lane < 8) red[12 * lane + warp] = k;
        asm volatile("bar.arrive 6, %0;" ::"n"(32 * (NCW + 2)) : "memory");
    }
}

typedef CUresult (*EncodeFn)(CUtensorMap*, CUtensorMapDataType, cuuint32_t, void*, const cuuint64_t*, const cuuint64_t*,
                             const cuuint32_t*, const cuuint32_t*, CUtensorMapInterleave, CUtensorMapSwizzle,
                             CUtensorMapL2promotion, CUtensorMapFloatOOBfill);

void make_map(EncodeFn enc, CUtensorMap* m, void* p, uint64_t cols, uint64_t rows, uint32_t bc, uint32_t br, CUtensorMapSwizzle sw,
              CUtensorMapL2promotion promo = CU_TENSOR_MAP_L2_PROMOTION_NONE) {
    cuuint64_t gd[2] = {cols, rows};
    cuuint64_t gs[1] = {cols * 2};
    cuuint32_t bd[2] = {bc, br};
    cuuint32_t es[2] = {1, 1};
    enc(m, CU_TENSOR_MAP_DATA_TYPE_BFLOAT16, 2, p, gd, gs, bd, es, CU_TENSOR_MAP_INTERLEAVE_NONE, sw,
        promo, CU_TENSOR_MAP_FLOAT_OOB_FILL_NONE);
}

}

extern "C" void kernel_launch(void* const* d_in, const int* in_sizes, int n_in, void* d_out, int out_size) {
    (void)in_sizes; (void)n_in; (void)out_size;
    EncodeFn enc = nullptr;
    cudaDriverEntryPointQueryResult qr;
    cudaGetDriverEntryPoint("cuTensorMapEncodeTiled", (void**)&enc, cudaEnableDefault, &qr);
    Maps maps;
    make_map(enc, &maps.k, d_in[1], 64, (uint64_t)HKV * SK * 2, 64, 2 * TILE, CU_TENSOR_MAP_SWIZZLE_128B);
    make_map(enc, &maps.v, d_in[2], 64, (uint64_t)HKV * SK * 2, 64, 2 * TILE, CU_TENSOR_MAP_SWIZZLE_128B);
    make_map(enc, &maps.wmod, d_in[10], 6 * DM, DM, 32, 64, CU_TENSOR_MAP_SWIZZLE_64B);
    make_map(enc, &maps.wq, d_in[3], 4096, DM, 32, 64, CU_TENSOR_MAP_SWIZZLE_64B);
    make_map(enc, &maps.wo, d_in[4], 64, 4096 * 9, 64, 72, CU_TENSOR_MAP_SWIZZLE_128B);
    make_map(enc, &maps.gate, d_in[6], FF, DM, 32, 64, CU_TENSOR_MAP_SWIZZLE_64B, CU_TENSOR_MAP_L2_PROMOTION_L2_128B);
    make_map(enc, &maps.up, d_in[7], FF, DM, 32, 64, CU_TENSOR_MAP_SWIZZLE_64B, CU_TENSOR_MAP_L2_PROMOTION_L2_128B);
    make_map(enc, &maps.gatex, d_in[6], FF, DM, 16, 64, CU_TENSOR_MAP_SWIZZLE_32B, CU_TENSOR_MAP_L2_PROMOTION_L2_128B);
    make_map(enc, &maps.upx, d_in[7], FF, DM, 16, 64, CU_TENSOR_MAP_SWIZZLE_32B, CU_TENSOR_MAP_L2_PROMOTION_L2_128B);
    make_map(enc, &maps.gb, d_in[10], 6 * DM, DM, 8, 192, CU_TENSOR_MAP_SWIZZLE_NONE);
    make_map(enc, &maps.down, d_in[8], 64, FF * 9, 64, 72, CU_TENSOR_MAP_SWIZZLE_128B);
    cudaFuncSetAttribute(fused_kernel, cudaFuncAttributeMaxDynamicSharedMemorySize, SMEM_BYTES);
    typedef const __nv_bfloat16* P;
    const Ptrs ptr = {(P)d_in[3] + 400 * 4096, (P)d_in[0], (P)d_in[9], (__nv_bfloat16*)d_out};
    fused_kernel<<<NCTA, NTHREADS, SMEM_BYTES, cudaStreamPerThread>>>(ptr, maps);
}
```

```cpp
#include <cuda_runtime.h>
#include <cuda_bf16.h>
#include <cuda.h>
#include <stdint.h>

namespace {

constexpr int DM = 576;
constexpr int SK = 65536;
constexpr int HKV = 16;
constexpr int FF = 4608;
constexpr int NCTA = 132;
constexpr int NQ = 128;
constexpr int MOD_C0 = 42;
constexpr int NRED = 72;
constexpr int C_X = 96, C_P = 120, C_E = 128;
constexpr int NY = C_X + (C_E - C_P);
constexpr int FX0 = 32 * NCTA;
static_assert(FX0 + 16 * (C_P - C_X) == FF && 40 * C_X == 256 * (HKV - 1), "weight split");

constexpr int TILE = 32;
constexpr int TPH = SK / TILE;
constexpr int NSTATIC = (HKV - 1) * TPH;
constexpr int GRP = 4;
constexpr int NG = NCTA / GRP;
constexpr int NPOOL = TPH;
constexpr int ITEM = TILE * 256;

constexpr int D_PRO = 5, N_PRO = 32;
constexpr int D_MAIN = 6;
constexpr int D_POOL = 5;
constexpr int D_CAP = 6;
constexpr int DMAX = 6;
constexpr float T_LEAD = 1.1f;
constexpr float T_GB = 0.3f;
constexpr int X1_GATE = 6;
constexpr int PF_BYTES = 8192;
constexpr int NPROBE = 14;

constexpr int NCW = 9;
constexpr int NAS = 8;
constexpr int NAP = 5;
constexpr int W_PROD = 9, W_RED = 10;
constexpr int NTHREADS = 12 * 32;

constexpr int OFF_WMOD = 0;
constexpr int OFF_WQ = 9 * 4096;
constexpr int OFF_WO = 0;
constexpr int OFF_GATEX = 0;
constexpr int OFF_UPX = 9 * 2048;
constexpr int OFF_GATE = 40 * 1152;
constexpr int OFF_UP = OFF_GATE + 9 * 4096;
constexpr int OFF_SLOT0 = 18 * 4096;
constexpr int OFF_RING = OFF_SLOT0 + 2 * (NAS - NAP) * ITEM;
constexpr int OFF_DOWN = OFF_RING;
constexpr int OFF_GB = OFF_DOWN + 48 * 1152;
constexpr int OFF_BAR = OFF_RING + 2 * NAP * ITEM;
constexpr int OFF_STAGE = OFF_BAR + 512;
constexpr int OFF_RED = OFF_STAGE + NAS * 260 * 4;
constexpr int OFF_Q = OFF_RED + 9 * (80 + 96) * 4;
constexpr int OFF_STAT = OFF_Q + 3 * 256 * 2;
constexpr int OFF_VEC = OFF_STAT + 2 * 20 * 4;
constexpr int OFF_SEL = OFF_VEC + 64 * 4;
constexpr int OFF_SILU = OFF_SEL + 96 * 4;
constexpr int OFF_NTOT = OFF_SILU + DM * 2;
constexpr int SMEM_BYTES = OFF_NTOT + 16;
static_assert(SMEM_BYTES <= 232448, "smem");
static_assert(OFF_UP + 9 * 4096 <= OFF_RING && OFF_GATE % 1024 == 0, "layout");

constexpr int B_EMPTY = 2 * NAS, B_WO = 4 * NAS, B_GU = B_WO + 5, B_DOWN = B_GU + 9, B_SDONE = B_DOWN + 3, B_PDONE = B_SDONE + 1,
              B_GB = B_PDONE + 1, B_SEL = B_GB + 1, B_Q2 = B_SEL + 1, B_WMOD = B_Q2 + 1, B_WQ = B_WMOD + 5, B_END = B_WQ + 5;
static_assert(B_END <= 64, "barriers");

constexpr float NEG_BIG = -3.0e38f;
constexpr uint32_t SPIN_LIMIT = 1u << 20;

struct Maps { CUtensorMap wmod, wq, k, v, wo, gate, up, gatex, upx, down, gb; };

__device__ uint32_t g_epoch;
__device__ __align__(128) uint32_t g_ticket[8];
__device__ __align__(128) uint32_t g_mod[5 * DM];
__device__ __align__(128) uint32_t g_q[4096];
__device__ __align__(128) uint32_t g_part[NCTA * 2 * 2 * 128];
__device__ __align__(128) uint32_t g_ml[2 * 2 * 144 * 4];
constexpr int BOX_P = 2 * NRED, BOX_X = BOX_P + 5 * 8, NBOX = BOX_X + 4;
constexpr int ZA = 20;
__device__ __align__(128) uint32_t g_boxes[(NBOX + 1) * 2048];
__device__ __align__(128) uint32_t g_sel[NRED + 8];

__device__ __forceinline__ void mbar_init(uint32_t b, uint32_t c) {
    asm volatile("mbarrier.init.shared::cta.b64 [%0], %1;" ::"r"(b), "r"(c) : "memory");
}
__device__ __forceinline__ void mbar_expect(uint32_t b, uint32_t bytes) {
    asm volatile("mbarrier.arrive.expect_tx.shared::cta.b64 _, [%0], %1;" ::"r"(b), "r"(bytes) : "memory");
}
__device__ __forceinline__ void mbar_arrive(uint32_t b) {
    asm volatile("mbarrier.arrive.shared::cta.b64 _, [%0];" ::"r"(b) : "memory");
}
__device__ __forceinline__ bool mbar_try(uint32_t b, uint32_t ph) {
    uint32_t ok;
    asm volatile("{\n.reg .pred p;\nmbarrier.try_wait.parity.shared::cta.b64 p, [%1], %2;\nselp.u32 %0, 1, 0, p;\n}"
                 : "=r"(ok) : "r"(b), "r"(ph) : "memory");
    return ok;
}
__device__ __forceinline__ bool mbar_test(uint32_t b, uint32_t ph) {
    uint32_t ok;
    asm volatile("{\n.reg .pred p;\nmbarrier.test_wait.parity.shared::cta.b64 p, [%1], %2;\nselp.u32 %0, 1, 0, p;\n}"
                 : "=r"(ok) : "r"(b), "r"(ph) : "memory");
    return ok;
}
__device__ __forceinline__ void mbar_wait(uint32_t b, uint32_t ph) {
    uint32_t n = 0;
    while (!mbar_try(b, ph)) { if (++n > SPIN_LIMIT) __trap(); }
}
__device__ __forceinline__ void tma2d(uint32_t dst, const CUtensorMap* m, int c0, int c1, uint32_t bar, uint64_t pol) {
    asm volatile("cp.async.bulk.tensor.2d.shared::cluster.global.mbarrier::complete_tx::bytes.L2::cache_hint "
                 "[%0], [%1, {%3, %4}], [%2], %5;"
                 ::"r"(dst), "l"(m), "r"(bar), "r"(c0), "r"(c1), "l"(pol) : "memory");
}
__device__ __forceinline__ void bar_sync(int id, int n) { asm volatile("bar.sync %0, %1;" ::"r"(id), "r"(n) : "memory"); }
__device__ __forceinline__ void ldsm4(uint32_t a, uint32_t (&r)[4]) {
    asm volatile("ldmatrix.sync.aligned.m8n8.x4.shared.b16 {%0,%1,%2,%3}, [%4];"
                 : "=r"(r[0]), "=r"(r[1]), "=r"(r[2]), "=r"(r[3]) : "r"(a) : "memory");
}
__device__ __forceinline__ void ldsm4t(uint32_t a, uint32_t (&r)[4]) {
    asm volatile("ldmatrix.sync.aligned.m8n8.x4.trans.shared.b16 {%0,%1,%2,%3}, [%4];"
                 : "=r"(r[0]), "=r"(r[1]), "=r"(r[2]), "=r"(r[3]) : "r"(a) : "memory");
}
__device__ __forceinline__ void mma16816(float (&c)[4], const uint32_t (&a)[4], uint32_t b0, uint32_t b1) {
    asm volatile("mma.sync.aligned.m16n8k16.row.col.f32.bf16.bf16.f32 {%0,%1,%2,%3}, {%4,%5,%6,%7}, {%8,%9}, {%0,%1,%2,%3};"
                 : "+f"(c[0]), "+f"(c[1]), "+f"(c[2]), "+f"(c[3])
                 : "r"(a[0]), "r"(a[1]), "r"(a[2]), "r"(a[3]), "r"(b0), "r"(b1));
}
__device__ __forceinline__ uint32_t movmat(uint32_t a) {
    uint32_t d; asm volatile("movmatrix.sync.aligned.m8n8.trans.b16 %0, %1;" : "=r"(d) : "r"(a)); return d;
}
__device__ __forceinline__ float ex2(float x) { float y; asm("ex2.approx.ftz.f32 %0, %1;" : "=f"(y) : "f"(x)); return y; }
__device__ __forceinline__ uint32_t pack2(float lo, float hi) {
    uint32_t r; asm("cvt.rn.bf16x2.f32 %0, %1, %2;" : "=r"(r) : "f"(hi), "f"(lo)); return r;
}
__device__ __forceinline__ float rbf(float x) { return __uint_as_float(pack2(0.f, x)); }
__device__ __forceinline__ float rcp(float x) { float y; asm("rcp.approx.ftz.f32 %0, %1;" : "=f"(y) : "f"(x)); return y; }
__device__ __forceinline__ float blo(uint32_t p) { return __uint_as_float(p << 16); }
__device__ __forceinline__ float bhi(uint32_t p) { return __uint_as_float(p & 0xffff0000u); }

__device__ __forceinline__ uint32_t tagw(float v, uint32_t tag) { return (__float_as_uint(v) & ~3u) | tag; }
__device__ __forceinline__ float untag(uint32_t w) { return __uint_as_float(w & ~3u); }
__device__ __forceinline__ void stg1(uint32_t* p, uint32_t a) {
    asm volatile("st.relaxed.gpu.global.u32 [%0], %1;" ::"l"(p), "r"(a) : "memory");
}
__device__ __forceinline__ void stg2(uint32_t* p, uint32_t a, uint32_t b) {
    asm volatile("st.relaxed.gpu.global.v2.u32 [%0], {%1,%2};" ::"l"(p), "r"(a), "r"(b) : "memory");
}
__device__ __forceinline__ void stg4(uint32_t* p, uint32_t a, uint32_t b, uint32_t c, uint32_t d) {
    asm volatile("st.relaxed.gpu.global.v4.u32 [%0], {%1,%2,%3,%4};" ::"l"(p), "r"(a), "r"(b), "r"(c), "r"(d) : "memory");
}
__device__ __forceinline__ void red1(uint32_t* p, uint32_t a) {
    asm volatile("red.relaxed.gpu.global.or.b32 [%0], %1;" ::"l"(p), "r"(a) : "memory");
}
__device__ __forceinline__ uint32_t ldg1(const uint32_t* p) {
    uint32_t v; asm volatile("ld.relaxed.gpu.global.u32 %0, [%1];" : "=r"(v) : "l"(p) : "memory"); return v;
}
__device__ __forceinline__ uint2 ldg2(const uint32_t* p) {
    uint2 v; asm volatile("ld.relaxed.gpu.global.v2.u32 {%0,%1}, [%2];" : "=r"(v.x), "=r"(v.y) : "l"(p) : "memory"); return v;
}
__device__ __forceinline__ uint4 ldg4(const uint32_t* p) {
    uint4 v;
    asm volatile("ld.relaxed.gpu.global.v4.u32 {%0,%1,%2,%3}, [%4];" : "=r"(v.x), "=r"(v.y), "=r"(v.z), "=r"(v.w) : "l"(p) : "memory");
    return v;
}
__device__ __forceinline__ uint32_t bad2(uint2 v, uint32_t tag) { return ((v.x ^ tag) | (v.y ^ tag)) & 3u; }
__device__ __forceinline__ uint32_t bad4(uint4 v, uint32_t tag) {
    return ((v.x ^ tag) | (v.y ^ tag) | (v.z ^ tag) | (v.w ^ tag)) & 3u;
}
__device__ __forceinline__ uint32_t clk() { uint32_t c; asm volatile("mov.u32 %0, %%clock;" : "=r"(c)); return c; }
__device__ __forceinline__ void spin_guard(uint32_t& n) { if (++n > SPIN_LIMIT) __trap(); }

__device__ __forceinline__ void ln_stats_part(float a, float b, float* stat, int warp, int lane) {
    const float ref = __shfl_sync(0xffffffffu, a, 0);
    a -= ref; b -= ref;
    float s = a + b, q = a * a + b * b;
#pragma unroll
    for (int o = 16; o; o >>= 1) { s += __shfl_xor_sync(0xffffffffu, s, o); q += __shfl_xor_sync(0xffffffffu, q, o); }
    const float d = s * (1.0f / 64);
    if (lane == 0) *reinterpret_cast<float2*>(stat + 2 * warp) = make_float2(ref + d, fmaf(-s, d, q));
}
__device__ __forceinline__ void ln_stats_fin(const float* stat, float& mean, float& rsd) {
    const float4 a = *reinterpret_cast<const float4*>(stat), b = *reinterpret_cast<const float4*>(stat + 4),
                 c = *reinterpret_cast<const float4*>(stat + 8), d = *reinterpret_cast<const float4*>(stat + 12);
    const float2 e = *reinterpret_cast<const float2*>(stat + 16);
    const float mu = (((a.x + a.z) + (b.x + b.z)) + ((c.x + c.z) + (d.x + d.z)) + e.x) * (1.0f / NCW);
    const float m2 = ((a.y + a.w) + (b.y + b.w)) + ((c.y + c.w) + (d.y + d.w)) + e.y;
#define SQ(v) (((v) - mu) * ((v) - mu))
    const float sp = ((SQ(a.x) + SQ(a.z)) + (SQ(b.x) + SQ(b.z))) + ((SQ(c.x) + SQ(c.z)) + (SQ(d.x) + SQ(d.z))) + SQ(e.x);
#undef SQ
    mean = rbf(mu);
    const float v = rbf(rbf(fmaxf(fmaf(64.0f, sp, m2), 0.f) * (1.0f / DM)) + 1e-5f);
    float sd;
    asm("sqrt.approx.ftz.f32 %0, %1;" : "=f"(sd) : "f"(v));
    rsd = rcp(rbf(sd));
}
__device__ __forceinline__ uint32_t ln_apply(float xa, float xb, float mean, float rsd, uint32_t scale1, uint32_t shift) {
    uint32_t p = pack2(xa - mean, xb - mean);
    p = pack2(blo(p) * rsd, bhi(p) * rsd);
    p = pack2(blo(p) * blo(scale1), bhi(p) * bhi(scale1));
    return pack2(blo(p) + blo(shift), bhi(p) + bhi(shift));
}

__device__ __forceinline__ void gemv32(uint32_t box, uint32_t vp, float* red, int lane) {
    const int r = lane & 7, mhi = (lane >> 3) & 1, khi = lane >> 4, tig = lane & 3, g = lane >> 2;
    float c[2][2][4] = {};
#pragma unroll
    for (int s = 0; s < 4; s++) {
        uint32_t b0 = __shfl_sync(0xffffffffu, vp, 8 * s + tig), b1 = __shfl_sync(0xffffffffu, vp, 8 * s + 4 + tig);
        const int row = 16 * s + 8 * khi + r;
#pragma unroll
        for (int i = 0; i < 2; i++) {
            uint32_t a[4];
            ldsm4t(box + row * 64 + (((2 * i + mhi) ^ (r >> 1)) << 4), a);
            mma16816(c[i][s & 1], a, b0, b1);
        }
    }
    const float v0 = (tig & 1) ? c[0][0][2] + c[0][1][2] : c[0][0][0] + c[0][1][0];
    const float v1 = (tig & 1) ? c[1][0][2] + c[1][1][2] : c[1][0][0] + c[1][1][0];
    red[8 * tig + g] = (tig & 2) ? v1 : v0;
}
__device__ __forceinline__ float sum9(const float* p) {
    return (((p[0] + p[80]) + (p[160] + p[240])) + ((p[320] + p[400]) + (p[480] + p[560]))) + p[640];
}

__device__ __forceinline__ void load_frags64(uint32_t base, int s, bool half, int w, int lane, uint32_t (&a)[4][4]) {
    const int r = lane & 7, mhi = (lane >> 3) & 1, khi = half ? 0 : lane >> 4;
    const int row = 16 * s + 8 * khi + r;
    const uint32_t line = base + (9 * row + w) * 128, x = mhi ^ ((row + w) & 7);
#pragma unroll
    for (int i = 0; i < 4; i++) ldsm4t(line + (((2 * i) ^ x) << 4), a[i]);
}
__device__ __forceinline__ void pick2(const float (&c)[4][4], int tig, float& v0, float& v1) {
    v0 = (tig & 2) ? ((tig & 1) ? c[3][0] : c[2][0]) : ((tig & 1) ? c[1][0] : c[0][0]);
    v1 = (tig & 2) ? ((tig & 1) ? c[3][2] : c[2][2]) : ((tig & 1) ? c[1][2] : c[0][2]);
}

__device__ __forceinline__ int col8(int lane) { return 4 * (lane & 1) + (lane & 2) + ((lane >> 2) & 1); }
__device__ __forceinline__ float warp_cols(float a, float b, float c, float d, int lane) {
    const bool p = lane & 2, q = lane & 4;
    const float k0 = (p ? c : a) + __shfl_xor_sync(0xffffffffu, p ? a : c, 2);
    const float k1 = (p ? d : b) + __shfl_xor_sync(0xffffffffu, p ? b : d, 2);
    float k = (q ? k1 : k0) + __shfl_xor_sync(0xffffffffu, q ? k0 : k1, 4);
    k += __shfl_xor_sync(0xffffffffu, k, 8);
    return k + __shfl_xor_sync(0xffffffffu, k, 16);
}

__device__ __forceinline__ uint32_t* mbox(int b, uint32_t side) {
    const uintptr_t base = (reinterpret_cast<uintptr_t>(g_boxes) + 8191) & ~(uintptr_t)8191;
    return reinterpret_cast<uint32_t*>(base) + (2 * b + (side & 1u)) * 1024;
}
__device__ __forceinline__ int group_begin(int q) { return (NSTATIC * q) / NG; }
__device__ __forceinline__ void prefetch_map(const CUtensorMap* m) { asm volatile("prefetch.tensormap [%0];" ::"l"(m) : "memory"); }

struct Ptrs { const __nv_bfloat16 *pf, *x, *c; __nv_bfloat16* out; };

__global__ void __launch_bounds__(NTHREADS, 1)
fused_kernel(const __grid_constant__ Ptrs ptr, const __grid_constant__ Maps maps) {
    extern __shared__ __align__(1024) unsigned char smem[];
    asm volatile("{\n.reg .pred p;\n.reg .u32 t;\n.reg .u64 a;\nmov.u32 t, %%ctaid.x;\nmad.wide.u32 a, t, %1, %0;\nmov.u32 t, %%tid.x;\n"
                 "setp.eq.u32 p, t, 0;\n@p cp.async.bulk.prefetch.L2.global [a], %1;\n}" ::"l"(ptr.pf), "n"(PF_BYTES) : "memory");
    const uint32_t sb = (uint32_t)__cvta_generic_to_shared(smem);
    const int tid = threadIdx.x, warp = tid >> 5, lane = tid & 31, cta = blockIdx.x;
    const uint32_t bars = sb + OFF_BAR;
    volatile int* ntot = reinterpret_cast<volatile int*>(smem + OFF_NTOT);
    const bool has_mod = cta >= MOD_C0, has_q = cta < NQ;
    const bool stat_wo = cta < C_X, extra = cta >= C_X && cta < C_P, pool_head = cta >= C_P && cta < C_E;

    const int g0 = group_begin(cta / GRP), t0 = g0 + cta % GRP, t1 = group_begin(cta / GRP + 1);
    uint32_t xp = 0, cp = 0, epoch = 0;
    uint64_t pol = 0;
#define ISSUE_SLICE(i, map, off, bar, col)                                  \
    do {                                                                    \
        tma2d(sb + (off) + 8192 * (i), (map), (col), 128 * (i), (bar), pol); \
        if ((i) < 4) tma2d(sb + (off) + 8192 * (i) + 4096, (map), (col), 128 * (i) + 64, (bar), pol); \
    } while (0)
    if (tid == 0) {
        const CUtensorMap* m0 = has_mod ? &maps.wmod : &maps.wq;
        prefetch_map(m0);
        const uint32_t b0 = bars + 8 * (has_mod ? B_WMOD : B_WQ), off = has_mod ? OFF_WMOD : OFF_WQ;
        const int col = 32 * (has_mod ? cta - MOD_C0 : cta);
#pragma unroll
        for (int i = 0; i < 5; i++) mbar_init(b0 + 8 * i, 1);
        asm volatile("fence.proxy.async.shared::cta;" ::: "memory");
        asm volatile("createpolicy.fractional.L2::evict_first.b64 %0, 1.0;" : "=l"(pol));
#pragma unroll
        for (int i = 0; i < 5; i++) {
            mbar_expect(b0 + 8 * i, i < 4 ? 8192 : 4096);
            ISSUE_SLICE(i, m0, off, b0 + 8 * i, col);
        }
    }
    __syncwarp();
    if (tid == 32 * W_RED) {
#pragma unroll
        for (int b = 0; b < 27; b++) mbar_init(bars + 8 * b, 1);
        asm volatile("fence.proxy.async.shared::cta;" ::: "memory");
    } else if (tid == 32 * W_PROD) {
        prefetch_map(&maps.wq);
        prefetch_map(&maps.k);
        prefetch_map(&maps.v);
        if (has_mod) {
#pragma unroll
            for (int b = B_WQ; b < B_END; b++) mbar_init(bars + 8 * b, 1);
        }
        asm volatile("fence.proxy.async.shared::cta;" ::: "memory");
        asm volatile("createpolicy.fractional.L2::evict_first.b64 %0, 1.0;" : "=l"(pol));
    } else if (tid == 32 * W_RED + 32) {
#pragma unroll
        for (int b = 27; b < B_WMOD; b++) mbar_init(bars + 8 * b, b >= B_DOWN && b < B_SDONE ? 2 : 1);
        asm volatile("fence.proxy.async.shared::cta;" ::: "memory");
        *ntot = 0x7fffffff;
    } else if (warp < NCW) {
        asm volatile("ld.global.nc.u32 %0, [%1];" : "=r"(cp) : "l"(ptr.c + 2 * tid));
        asm volatile("ld.global.nc.u32 %0, [%1];" : "=r"(xp) : "l"(ptr.x + 2 * tid));
        if (warp == 0) {
            if (has_mod) stg1(g_mod + 32 * (cta - MOD_C0) + lane, 0);
            if (has_q) stg1(g_q + 32 * cta + lane, 0);
        }
    }
    __syncwarp();
    if (warp != W_PROD) asm volatile("ld.relaxed.gpu.global.u32 %0, [%1];" : "=r"(epoch) : "l"(&g_epoch) : "memory");
    __syncthreads();

    const int head0 = g0 / TPH;
    const int last_seg = t1 > (head0 + 1) * TPH;
    const int n0 = (min(t1, (head0 + 1) * TPH) - t0 + GRP - 1) / GRP;
    const int n01 = (t1 - t0 + GRP - 1) / GRP;
    const int woff = (-n01) & (NAS - 1);

    if (warp == W_PROD) {
        if (lane == 0) {
            if (sb & 1023) __trap();
            const uint32_t c_start = clk();
            uint32_t hist[DMAX];
#pragma unroll
            for (int i = 0; i < DMAX; i++) hist[i] = bars + 8 * ((has_mod ? B_WMOD : B_WQ) + max(4 - i, 0));
#define WAIT_LANDED(D) mbar_wait(hist[(D) - 1] & ~1u, hist[(D) - 1] & 1u)
#define PUSH_ITEM(bar, par)                                                 \
            do {                                                            \
                _Pragma("unroll") for (int i_ = DMAX - 1; i_ > 0; i_--) hist[i_] = hist[i_ - 1]; \
                hist[0] = (bar) | (par);                                    \
            } while (0)
            uint32_t phm = 0;
#define ISSUE_TILE(D, i)                                                    \
            do {                                                            \
                const int w_ = ((i) + woff) & (NAS - 1);                    \
                const uint32_t ph_ = (phm >> w_) & 1u;                      \
                const uint32_t fb_ = bars + 16 * w_, dst_ = sb + OFF_SLOT0 + ((w_ + NAS - NAP) & (NAS - 1)) * (2 * ITEM); \
                phm ^= 1u << w_;                                            \
                _Pragma("unroll") for (int kv_ = 0; kv_ < 2; kv_++) {       \
                    mbar_wait(fb_ + 8 * (B_EMPTY + kv_), ph_ ^ 1);          \
                    mbar_expect(fb_ + 8 * kv_, ITEM);                       \
                    WAIT_LANDED(D);                                         \
                    tma2d(dst_ + kv_ * ITEM, kv_ ? &maps.v : &maps.k, 0, (t0 + GRP * (i)) * (2 * TILE), fb_ + 8 * kv_, pol); \
                    PUSH_ITEM(fb_ + 8 * kv_, ph_);                          \
                }                                                           \
            } while (0)

            if (has_mod && has_q) {
#pragma unroll 1
                for (int i = 0; i < 5; i++) {
                    const uint32_t bar = bars + 8 * (B_WQ + i);
                    mbar_expect(bar, i < 4 ? 8192 : 4096);
                    WAIT_LANDED(D_PRO);
                    ISSUE_SLICE(i, &maps.wq, OFF_WQ, bar, 32 * cta);
                    PUSH_ITEM(bar, 0u);
                }
            }
#pragma unroll 1
            for (int i = 0; i < N_PRO; i++) {
                if (i == NAS) {
#pragma unroll
                    for (int k = 0; k < D_PRO; k++) {
                        bool free;
                        uint32_t n = 0;
                        while (!(free = mbar_test(bars + 16 * woff + 8 * B_EMPTY, 0)) && !mbar_test(hist[D_PRO - 1 - k], 0)) spin_guard(n);
                        if (free) break;
                        asm volatile("cp.async.bulk.prefetch.tensor.2d.L2.global.L2::cache_hint [%0, {0, %1}], %2;"
                                     ::"l"((k & 1) ? &maps.v : &maps.k), "r"((t0 + GRP * (NAS + k / 2)) * (2 * TILE)), "l"(pol) : "memory");
                    }
                }
                ISSUE_TILE(D_PRO, i);
            }
#pragma unroll 1
            for (int i = N_PRO; i < n01; i++) ISSUE_TILE(D_MAIN, i);

            prefetch_map(&maps.wo); prefetch_map(&maps.gate); prefetch_map(&maps.up); prefetch_map(&maps.down);
            if (extra) { prefetch_map(&maps.gatex); prefetch_map(&maps.upx); }
            if (cta < NRED) prefetch_map(&maps.gb);
            if (pool_head) {
#pragma unroll 1
                for (int i = 0; i < 4; i++) {
                    const uint32_t bar = bars + 8 * (B_WO + i);
                    mbar_expect(bar, 9216);
                    WAIT_LANDED(D_POOL);
                    tma2d(sb + OFF_WO + 9216 * i, &maps.wo, 0, 9 * (32 * cta + 8 * i), bar, pol);
                    PUSH_ITEM(bar, 0u);
                }
            }
            mbar_wait(bars + 8 * B_SEL, 0);
            uint32_t c_tk = 0, left = 0;
            int n = 0, w = 0;
#pragma unroll 1
            while (true) {
                const uint32_t ph = (phm >> w) & 1u, fb = bars + 16 * w, dst = sb + OFF_RING + w * (2 * ITEM);
                WAIT_LANDED(D_POOL);
                const uint32_t tk = atomicAdd(g_ticket, 1u);
                mbar_wait(fb + 8 * (B_EMPTY + 1), ph ^ 1);
                if (tk >= (uint32_t)NPOOL) break;
                mbar_expect(fb, ITEM);
                tma2d(dst, &maps.k, 0, (NSTATIC + (int)tk) * (2 * TILE), fb, pol);
                mbar_expect(fb + 8, ITEM);
                tma2d(dst + ITEM, &maps.v, 0, (NSTATIC + (int)tk) * (2 * TILE), fb + 8, pol);
                c_tk = clk();
                left = NPOOL - tk;
                PUSH_ITEM(fb, ph);
                PUSH_ITEM(fb + 8, ph);
                phm ^= 1u << w;
                n++;
                if (++w == NAP) w = 0;
            }
            *ntot = n;

            uint32_t due = clk();
            const float cpm = fminf((float)(due - c_start) * (1.0f / 540.0f), 4000.f);
            if (n) { const uint32_t dry = c_tk + (uint32_t)(cpm * (2 * ITEM * 1e-6f) * left); if ((int)(due - dry) > 0) due = dry; }
            due += (uint32_t)(cpm * T_LEAD);
#define WAIT_DUE(step)                                                      \
            do {                                                            \
                WAIT_LANDED(D_CAP);                                         \
                while ((int)(clk() - due) < 0) {}                           \
                due += (step);                                              \
            } while (0)
            uint32_t step = (uint32_t)(cpm * (C_X * 9216e-6f));
            if (stat_wo) {
#pragma unroll 1
                for (int i = 0; i < 5; i++) {
                    const uint32_t bar = bars + 8 * (B_WO + i);
                    mbar_expect(bar, 9216);
                    WAIT_DUE(step);
                    tma2d(sb + OFF_WO + 9216 * i, &maps.wo, 0, 9 * (40 * cta + 8 * i), bar, pol);
                    PUSH_ITEM(bar, 0u);
                }
            } else {
                due += 5 * step;
            }
            mbar_wait(bars + 8 * B_SDONE, 0);
            step = (uint32_t)(cpm * (64 * FF * 4e-6f));
            const int xcol = FX0 + 16 * (cta - C_X);
#pragma unroll 1
            for (int i = 0; i < 9; i++) {
                const uint32_t bar = bars + 8 * (B_GU + i);
                mbar_expect(bar, extra ? 12288 : 8192);
                WAIT_DUE(step);
                tma2d(sb + OFF_GATE + 4096 * i, &maps.gate, 32 * cta, 64 * i, bar, pol);
                tma2d(sb + OFF_UP + 4096 * i, &maps.up, 32 * cta, 64 * i, bar, pol);
                if (extra) {
                    tma2d(sb + OFF_GATEX + 2048 * i, &maps.gatex, xcol, 64 * i, bar, pol);
                    tma2d(sb + OFF_UPX + 2048 * i, &maps.upx, xcol, 64 * i, bar, pol);
                }
                PUSH_ITEM(bar, 0u);
            }
            mbar_wait(bars + 8 * B_PDONE, 0);
            step = (uint32_t)(cpm * (FF * 1152e-6f / 4) * (extra ? 0.6f : 1.0f));
#pragma unroll 1
            for (int i = 0; i < (extra ? 6 : 4); i++) {
                const uint32_t bar = bars + 8 * (B_DOWN + (i >> 1));
                mbar_expect(bar, 9216);
                WAIT_DUE(step);
                tma2d(sb + OFF_DOWN + 9216 * i, &maps.down, 0, 9 * (i < 4 ? 32 * cta + 8 * i : xcol + 8 * (i - 4)), bar, pol);
                PUSH_ITEM(bar, 0u);
            }
            if (cta < NRED) {
                const uint32_t bar = bars + 8 * B_GB;
                mbar_expect(bar, DM * 16);
                due += (uint32_t)(cpm * T_GB);
                WAIT_DUE(0);
#pragma unroll
                for (int i = 0; i < 3; i++) tma2d(sb + OFF_GB + 3072 * i, &maps.gb, 5 * DM + 8 * cta, 192 * i, bar, pol);
            }
        }
        return;
    }

    const uint32_t tag = epoch >= 3u ? 1u : epoch + 1u;

    if (warp >= W_RED) {
        const int half = warp - W_RED, col = 8 * cta + col8(lane);
        uint32_t* vec = reinterpret_cast<uint32_t*>(smem + OFF_VEC);
        uint32_t* sel = reinterpret_cast<uint32_t*>(smem + OFF_SEL);
        {
            const int nb = cta < NRED ? 2 : pool_head ? 5 : 0, b0 = cta < NRED ? 2 * cta : BOX_P + 5 * (cta - C_P);
            bar_sync(3, 32 * (NCW + 2));
            uint32_t* const pw = mbox(lane < nb ? b0 + lane : BOX_X + (cta & 3), half) + DM + 8 * ((cta >> 2) & 7);
            if (lane <= nb) {
#pragma unroll 1
                for (int j = 0; j < 7; j++) { stg4(pw + 64 * j, 0, 0, 0, 0); stg4(pw + 64 * j + 4, 0, 0, 0, 0); }
            }
            uint32_t best = ~0u;
#pragma unroll 1
            for (int r = 0; r < NPROBE * (nb + 1); r++) {
                if (lane == r % (nb + 1)) {
                    uint32_t* const q = pw + 64 * (r % 7);
                    const uint32_t c0 = clk();
                    uint32_t v, c1;
                    asm volatile("atom.relaxed.gpu.global.add.u32 %0, [%1], 4;" : "=r"(v) : "l"(q) : "memory");
                    asm volatile("{\n.reg .pred p;\nsetp.eq.u32 p, %1, 0xffffffff;\n@p trap;\nmov.u32 %0, %%clock;\n}" : "=r"(c1) : "r"(v) : "memory");
                    best = min(best, c1 - c0);
                }
                __syncwarp();
            }
            if (lane < 8) sel[80 + 8 * half + lane] = best;
            bar_sync(5, 64);
            const uint32_t sides = __ballot_sync(0xffffffffu, lane <= nb && sel[88 + (lane & 7)] < sel[80 + (lane & 7)]);
            for (int b = 0; b < nb; b++) {
                uint32_t* q = mbox(b0 + b, sides >> b) + 4 * (32 * half + lane);
#pragma unroll
                for (int i = 0; i < 4; i++) stg4(q + 256 * i, 0, 0, 0, 0);
            }
            if (cta == 0 && half && lane < 2) stg4(g_ticket + 4 * lane, 0, 0, 0, 0);
            __threadfence();
            bar_sync(5, 64);
            if (!half && lane == 0) {
                if (nb) stg1(g_sel + (cta < NRED ? cta : NRED + cta - C_P), (sides << 2) | tag);
                sel[80] = sides >> nb;
            }
            for (int i = 32 * half + lane; i < NRED + 8; i += 64) {
                uint32_t v, n = 0;
                do { __nanosleep(4000); v = ldg1(g_sel + i); spin_guard(n); } while ((v ^ tag) & 3u);
                sel[i] = v >> 2;
            }
            __threadfence();
            if (!half && lane == 0) mbar_arrive(bars + 8 * B_SEL);
        }
        bar_sync(3, 32 * (NCW + 2));
        float x1 = 0.f;
        if (cta < NRED) {
            uint32_t* const xs = mbox(BOX_X + (lane >> 3), 0) + col;
            const float x0 = __bfloat162float(ptr.x[col]);
            uint32_t ga, n = 0, bad;
            do { ga = ldg1(g_mod + 2 * DM + col); spin_guard(n); } while ((ga ^ tag) & 3u);
            const int t = 32 * half + lane;
            const uint32_t* src = mbox(2 * cta, sel[cta]) + 4 * t;
            uint4 v[4];
#pragma unroll
            for (int i = 0; i < 4; i++) {
                const uint32_t w = 64 * i + t < 2 * NY ? 0 : tag;
                v[i] = make_uint4(w, w, w, w);
            }
            mbar_wait(bars + 8 * B_GU, 0);
            do {
#pragma unroll
                for (int i = 0; i < 4; i++) if (bad4(v[i], tag)) v[i] = ldg4(src + 256 * i);
                bad = bad4(v[0], tag) | bad4(v[1], tag) | bad4(v[2], tag) | bad4(v[3], tag);
                spin_guard(n);
            } while (bad);
            __syncwarp();
#define SUM4(f) ((untag(v[0].f) + untag(v[1].f)) + (untag(v[2].f) + untag(v[3].f)))
            const float k = warp_cols(SUM4(x), SUM4(y), SUM4(z), SUM4(w), lane);
#undef SUM4
            if (half) {
                if (lane < 8) vec[48 + lane] = __float_as_uint(k);
                asm volatile("bar.arrive 5, 64;" ::: "memory");
            } else {
                bar_sync(5, 64);
                x1 = rbf(x0 + rbf(untag(ga) * rbf(k + __uint_as_float(vec[48 + (lane & 7)]))));
                stg1(xs, __float_as_uint(x1) | tag);
                stg1(xs + 1024, __float_as_uint(x1) | tag);
                if (cta == 0 && lane == 0) g_epoch = tag;
            }
        }
        {
            const int pr = 12 * half + min(lane & 15, 11);
            const float* q = reinterpret_cast<const float*>(smem + OFF_RED) + 720 + 2 * pr + 48 * (lane >> 4);
            bar_sync(4, 32 * (NCW + 2));
            float2 v[NCW];
#pragma unroll
            for (int w = 0; w < NCW; w++) v[w] = *reinterpret_cast<const float2*>(q + 96 * w);
#define SUM9(f) ((((v[0].f + v[1].f) + (v[2].f + v[3].f)) + ((v[4].f + v[5].f) + (v[6].f + v[7].f))) + v[8].f)
            const uint32_t a = pack2(SUM9(x), SUM9(y)), b = __shfl_xor_sync(0xffffffffu, a, 16);
#undef SUM9
            if (lane < 12) vec[24 + pr] = pack2(blo(a) * blo(b), bhi(a) * bhi(b));
            asm volatile("bar.arrive 8, %0;" ::"n"(32 * (NCW + 2)) : "memory");
        }
        if (cta >= NRED) return;
        float* red = reinterpret_cast<float*>(smem + OFF_RED);
        {
            const int g = lane >> 2, tig = lane & 3;
            const uint32_t* sv = reinterpret_cast<const uint32_t*>(smem + OFF_SILU) + 144 * half + (g & 4) + tig;
            uint32_t bb[9][2];
#pragma unroll
            for (int t = 0; t < 9; t++) { bb[t][0] = sv[16 * t]; bb[t][1] = sv[16 * t + 8]; }
            mbar_wait(bars + 8 * B_GB, 0);
            float c[3][4] = {};
#pragma unroll
            for (int t = 0; t < 9; t++) {
                uint32_t a[4];
                ldsm4t(sb + OFF_GB + (288 * half + 32 * t + lane) * 16, a);
                mma16816(c[t % 3], a, bb[t][0], bb[t][1]);
            }
            if (!(tig & 1)) red[96 + 4 * g + 2 * half + (tig >> 1)] = tig ? c[0][2] + c[1][2] + c[2][2] : c[0][0] + c[1][0] + c[2][0];
        }
        if (half) {
            asm volatile("bar.arrive 6, %0;" ::"n"(32 * (NCW + 2)) : "memory");
        } else {
            const float* q = red + 12 * (lane & 7);
            bar_sync(6, 32 * (NCW + 2));
            const float4 a = *reinterpret_cast<const float4*>(q), b = *reinterpret_cast<const float4*>(q + 4);
            const float d = rbf((((a.x + a.y) + (a.z + a.w)) + ((b.x + b.y) + (b.z + b.w))) + q[8]);
            const float4 e = *reinterpret_cast<const float4*>(red + 96 + 4 * col8(lane));
            const float gb = rbf((e.x + e.y) + (e.z + e.w));
            if (lane < 8) ptr.out[col] = __float2bfloat16_rn(x1 + rbf(gb * d));
        }
        return;
    }

    float* red = reinterpret_cast<float*>(smem + OFF_RED);
    float* stat = reinterpret_cast<float*>(smem + OFF_STAT);
    const int g = lane >> 2, tig = lane & 3;
    uint32_t cb1 = 0, sbp = 0;
    {
        const float xa = blo(xp), xb = bhi(xp);
        ln_stats_part(xa, xb, stat, warp, lane);
        const float ca = blo(cp), cb = bhi(cp);
        cp = pack2(ca * rcp(1.0f + ex2(-1.4426950408889634f * ca)), cb * rcp(1.0f + ex2(-1.4426950408889634f * cb)));
        reinterpret_cast<uint32_t*>(smem + OFF_SILU)[tid] = cp;
        if (has_mod) {
            mbar_wait(bars + 8 * (B_WMOD + (warp >> 1)), 0);
            gemv32(sb + OFF_WMOD + 4096 * warp, cp, red + 80 * warp, lane);
        }
        bar_sync(2, 32 * NCW);
        if (has_mod && warp == 0) red1(g_mod + 32 * (cta - MOD_C0) + lane, __float_as_uint(rbf(sum9(red + lane))) | tag);
        if (has_q) {
            float mean, rsd;
            ln_stats_fin(stat, mean, rsd);
            mbar_wait(bars + 8 * (B_WQ + (warp >> 1)), 0);
            uint2 sa, sc;
            uint32_t n = 0;
            do { sa = ldg2(g_mod + 2 * tid); sc = ldg2(g_mod + DM + 2 * tid); spin_guard(n); } while (bad2(sa, tag) | bad2(sc, tag));
            const uint32_t hp = ln_apply(xa, xb, mean, rsd, pack2(1.0f + untag(sc.x), 1.0f + untag(sc.y)), __byte_perm(sa.x, sa.y, 0x7632));
            __syncwarp();
            gemv32(sb + OFF_WQ + 4096 * warp, hp, red + 720 + 80 * warp, lane);
            bar_sync(2, 32 * NCW);
            if (warp == 0) red1(g_q + 32 * cta + lane, __float_as_uint(rbf(sum9(red + 720 + lane))) | tag);
        }
        {
            uint4 v = make_uint4(tag, tag, tag, tag);
            uint2 s2 = make_uint2(0, 0), c2 = s2;
            uint32_t n = 0;
            do {
                if (tid < 64) v = ldg4(g_q + 256 * head0 + 4 * tid);
                if (bad2(s2, tag) | bad2(c2, tag)) { s2 = ldg2(g_mod + 3 * DM + 2 * tid); c2 = ldg2(g_mod + 4 * DM + 2 * tid); }
                spin_guard(n);
            } while (bad4(v, tag) | bad2(s2, tag) | bad2(c2, tag));
            if (tid < 64)
                *reinterpret_cast<uint2*>(smem + OFF_Q + 8 * tid) = make_uint2(__byte_perm(v.x, v.y, 0x7632), __byte_perm(v.z, v.w, 0x7632));
            sbp = __byte_perm(s2.x, s2.y, 0x7632);
            cb1 = pack2(1.0f + untag(c2.x), 1.0f + untag(c2.y));
        }
        bar_sync(3, 32 * (NCW + 2));
    }
    const uint32_t* sel = reinterpret_cast<const uint32_t*>(smem + OFF_SEL);

    if (warp < NAS) {
        const int r = lane & 7, var = r >> 2;
        const uint32_t kofs = (r + 8 * ((lane >> 3) & 1)) * 256, kx = (lane >> 4) ^ var ^ (2 * (r & 3));
        const uint32_t vofs = (r + 8 * (lane >> 4)) * 256, vx = ((lane >> 3) & 1) ^ var ^ (2 * (r & 3));
        const bool valid = (tig & 1) == (g >> 2);
        float* stage = reinterpret_cast<float*>(smem + OFF_STAGE);
        const uint32_t slot = sb + OFF_SLOT0 + ((warp + NAS - NAP) & (NAS - 1)) * (2 * ITEM);
        const uint32_t kb = slot + kofs, vb = slot + ITEM + vofs;
        const uint32_t kfull = bars + 16 * warp, kempty = kfull + 8 * B_EMPTY;
        int i = (warp - woff) & (NAS - 1);
        uint32_t ph = 0;
#pragma unroll 1
        for (int seg = 0; seg < 3; seg++) {
            if (seg == 1 && !last_seg) continue;
            if (seg == 2) {
                if (warp >= NAP) break;
                i = warp;
            }
            uint32_t qf[8][2];
            {
                if (seg) mbar_wait(bars + 8 * B_Q2, 0);
                const uint32_t* qs = reinterpret_cast<const uint32_t*>(smem + OFF_Q) + 128 * seg + 64 * (g & 1) + tig;
                const int qv = (g >> 1) & 1;
#pragma unroll
                for (int s = 0; s < 8; s++) { qf[s][0] = qs[8 * s + 4 * qv]; qf[s][1] = qs[8 * s + 4 * (qv ^ 1)]; }
            }
            float o[8][4] = {};
            float m0 = NEG_BIG, m1 = NEG_BIG, l0 = 0.f, l1 = 0.f;
            const int end = seg == 0 ? n0 : n01;
            const int nw = seg == 2 ? NAP : NAS;
#pragma unroll 1
            for (;; i += nw) {
                if (seg < 2) {
                    if (i >= end) break;
                    mbar_wait(kfull, ph);
                } else {
                    bool stop = false;
                    uint32_t n = 0;
                    while (true) {
                        if (i >= *ntot) { stop = true; break; }
                        if (mbar_test(kfull, ph)) break;
                        spin_guard(n);
                    }
                    if (__any_sync(0xffffffffu, stop)) break;
                }
                float s[2][2][4] = {};
#pragma unroll
                for (int st = 0; st < 8; st++) {
#pragma unroll
                    for (int mt = 0; mt < 2; mt++) {
                        uint32_t a[4];
                        ldsm4(kb + mt * 4096 + (st >> 2) * 128 + (((2 * (st & 3)) ^ (st >> 2) ^ kx) << 4), a);
                        mma16816(s[mt][st & 1], a, qf[st][0], qf[st][1]);
                    }
                }
                __syncwarp();
                if (lane == 0) mbar_arrive(kempty);
                float t[2][4];
#pragma unroll
                for (int mt = 0; mt < 2; mt++)
#pragma unroll
                    for (int j = 0; j < 4; j += 2) {
                        uint32_t p = pack2(s[mt][0][j] + s[mt][1][j], s[mt][0][j + 1] + s[mt][1][j + 1]);
                        p = pack2(blo(p) * 0.08838834764831845f, bhi(p) * 0.08838834764831845f);
                        if (!valid) p = 0xff80ff80u;
                        t[mt][j] = blo(p) * 1.4426950408889634f;
                        t[mt][j + 1] = bhi(p) * 1.4426950408889634f;
                    }
                float x0 = fmaxf(fmaxf(t[0][0], t[0][2]), fmaxf(t[1][0], t[1][2]));
                float x1 = fmaxf(fmaxf(t[0][1], t[0][3]), fmaxf(t[1][1], t[1][3]));
                if (__any_sync(0xffffffffu, x0 > m0 || x1 > m1)) {
#pragma unroll
                    for (int d = 16; d; d >>= 1) {
                        x0 = fmaxf(x0, __shfl_xor_sync(0xffffffffu, x0, d));
                        x1 = fmaxf(x1, __shfl_xor_sync(0xffffffffu, x1, d));
                    }
                    x0 = fmaxf(x0, m0); x1 = fmaxf(x1, m1);
                    const float a0 = ex2(m0 - x0), a1 = ex2(m1 - x1);
                    m0 = x0; m1 = x1;
                    l0 *= a0; l1 *= a1;
#pragma unroll
                    for (int j = 0; j < 8; j++) { o[j][0] *= a0; o[j][1] *= a1; o[j][2] *= a0; o[j][3] *= a1; }
                }
                uint32_t pb[2][2];
#pragma unroll
                for (int mt = 0; mt < 2; mt++) {
                    const float p0 = ex2(t[mt][0] - m0), p1 = ex2(t[mt][1] - m1), p2 = ex2(t[mt][2] - m0), p3 = ex2(t[mt][3] - m1);
                    l0 += p0 + p2; l1 += p1 + p3;
                    uint32_t h0 = pack2(p0, p1), h1 = pack2(p2, p3);
                    if (tig & 2) { h0 = pack2(p0 - blo(h0), p1 - bhi(h0)); h1 = pack2(p2 - blo(h1), p3 - bhi(h1)); }
                    pb[mt][0] = movmat(h0);
                    pb[mt][1] = movmat(h1);
                }
                mbar_wait(kfull + 8, ph);
#pragma unroll
                for (int mt = 0; mt < 2; mt++) {
#pragma unroll
                    for (int j = 0; j < 8; j++) {
                        uint32_t a[4];
                        ldsm4t(vb + mt * 4096 + (j >> 2) * 128 + (((2 * (j & 3)) ^ (j >> 2) ^ vx) << 4), a);
                        mma16816(o[j], a, pb[mt][0], pb[mt][1]);
                    }
                }
                __syncwarp();
                if (lane == 0) mbar_arrive(kempty + 8);
                ph ^= 1;
            }
            l0 += __shfl_xor_sync(0xffffffffu, l0, 17); l1 += __shfl_xor_sync(0xffffffffu, l1, 17);
            float* sw = stage + 260 * warp;
#pragma unroll
            for (int j = 0; j < 8; j++) {
                const float u0 = o[j][0] + __shfl_xor_sync(0xffffffffu, o[j][2], 1);
                const float u1 = o[j][1] + __shfl_xor_sync(0xffffffffu, o[j][3], 1);
                sw[64 * (tig & 2) + 16 * j + 8 * (tig & 1) + g] = ((tig & 2) ? u1 : u0) + __shfl_xor_sync(0xffffffffu, (tig & 2) ? u0 : u1, 2);
                if (j == 2 || j == 5) {
                    l0 += __shfl_xor_sync(0xffffffffu, l0, j == 2 ? 4 : 8);
                    l1 += __shfl_xor_sync(0xffffffffu, l1, j == 2 ? 4 : 8);
                }
            }
            if (lane == 0) *reinterpret_cast<float4*>(sw + 256) = make_float4(m0, l0, m1, l1);
            bar_sync(1, 32 * nw);
            if (tid == 128 && seg >= last_seg) mbar_arrive(bars + 8 * (seg == 2 ? B_PDONE : B_SDONE));
            if (tid < 128) {
                const int h = tid >> 6;
                float2 ml[NAS], ov[NAS];
                float M = NEG_BIG;
#pragma unroll
                for (int w = 0; w < NAS; w++) {
                    ml[w] = make_float2(NEG_BIG, 0.f); ov[w] = make_float2(0.f, 0.f);
                    if (w < NAP || seg < 2) {
                        ml[w] = *reinterpret_cast<const float2*>(stage + 260 * w + 256 + 2 * h);
                        ov[w] = *reinterpret_cast<const float2*>(stage + 260 * w + 2 * tid);
                    }
                    M = fmaxf(M, ml[w].x);
                }
                float a = 0.f, b = 0.f, L = 0.f;
#pragma unroll
                for (int w = 0; w < NAS; w++) {
                    const float e = ex2(ml[w].x - M);
                    a += e * ov[w].x; b += e * ov[w].y; L += e * ml[w].y;
                }
                const uint32_t w0 = tagw(M, tag), w1 = (__float_as_uint(M) << 2) | tag, w2 = tagw(L, tag);
                if (seg == 2) {
                    const int p = tid >> 4, k = cta / 28;
                    uint32_t* q = mbox(BOX_P + 5 * p + k, sel[NRED + p] >> k);
                    stg2(q + 32 * (cta % 28) + 2 * (tid & 15), tagw(a, tag), tagw(b, tag));
                    if ((tid & 15) == 0) stg4(q + 896 + 4 * (cta % 28), w0, w1, w2, w2);
                } else {
                    stg2(g_part + (cta * 2 + seg) * 256 + 2 * tid, tagw(a, tag), tagw(b, tag));
                    if ((tid & 63) == 0) stg4(g_ml + ((seg * 2 + h) * 144 + cta) * 4, w0, w1, w2, w2);
                }
            }
            if (seg < 2) { if (seg == last_seg) bar_sync(3, 32 * (NCW + 2)); else bar_sync(1, 32 * NAS); }
        }
    } else {
#pragma unroll 1
        for (int k = 0; k < 4; k++) {
            uint4 v;
            uint32_t n = 0;
            do {
                __nanosleep(1000);
                v = ldg4(g_q + 256 * (k < 2 ? head0 + 1 : HKV - 1) + 128 * (k & 1) + 4 * lane);
                spin_guard(n);
            } while (bad4(v, tag));
            *reinterpret_cast<uint2*>(smem + OFF_Q + 512 + 256 * k + 8 * lane) =
                make_uint2(__byte_perm(v.x, v.y, 0x7632), __byte_perm(v.z, v.w, 0x7632));
        }
        __syncwarp();
        if (lane == 0) mbar_arrive(bars + 8 * B_Q2);
        bar_sync(3, 32 * (NCW + 2));
    }
    const int r0 = 8 * warp + 2 * tig;
    const uint32_t sel0 = sel[r0], sel1 = sel[r0 + 1];
#define PUBLISH_Y(j)                                                        \
    do {                                                                    \
        stg1(mbox(2 * r0, sel0) + 8 * (j) + g, tagw(v0, tag));               \
        stg1(mbox(2 * r0 + 2, sel1) + 8 * (j) + g, tagw(v1, tag));           \
    } while (0)

    uint32_t* vec = reinterpret_cast<uint32_t*>(smem + OFF_VEC);
    if (stat_wo) {
        const int u = tid - 32 * NAP;
        if (u >= 0 && u < 40) {
            const int row = 40 * cta + u, kvh = row >> 8, h = (row >> 7) & 1;
            int q = (kvh * TPH * NG) / NSTATIC;
            while (group_begin(q + 1) <= kvh * TPH) q++;
            while (group_begin(q) > kvh * TPH) q--;
            float M = NEG_BIG, num = 0.f, den = 0.f;
#pragma unroll 1
            for (; group_begin(q) < (kvh + 1) * TPH; q++) {
                const int seg = group_begin(q) / TPH == kvh ? 0 : 1;
                uint4 ml[GRP];
                uint32_t ov[GRP], bad, spin = 0;
                while (true) {
                    bad = 0;
#pragma unroll
                    for (int k = 0; k < GRP; k++) {
                        ov[k] = ldg1(g_part + ((GRP * q + k) * 2 + seg) * 256 + (row & 255));
                        ml[k] = ldg4(g_ml + ((seg * 2 + h) * 144 + GRP * q + k) * 4);
                    }
#pragma unroll
                    for (int k = 0; k < GRP; k++) bad |= bad4(ml[k], tag) | ((ov[k] ^ tag) & 3u);
                    if (!bad) break;
                    __nanosleep(300);
                    spin_guard(spin);
                }
#pragma unroll
                for (int k = 0; k < GRP; k++) {
                    const float m = __uint_as_float((ml[k].x & ~3u) | ((ml[k].y >> 2) & 3u)), Mn = fmaxf(M, m);
                    const float e0 = ex2(M - Mn), e1 = ex2(m - Mn);
                    num = num * e0 + e1 * untag(ov[k]);
                    den = den * e0 + e1 * untag(ml[k].z);
                    M = Mn;
                }
            }
            reinterpret_cast<uint16_t*>(vec)[u] = (uint16_t)pack2(num * rcp(den), 0.f);
        }
        bar_sync(2, 32 * NCW);
        float c[4][4] = {};
#pragma unroll
        for (int s = 0; s < 3; s++) {
            const uint32_t b0 = vec[8 * s + tig], b1 = s < 2 ? vec[8 * s + 4 + tig] : 0u;
            uint32_t a[4][4];
            mbar_wait(bars + 8 * (B_WO + 2 * s), 0);
            if (s < 2) mbar_wait(bars + 8 * (B_WO + 2 * s + 1), 0);
            load_frags64(sb + OFF_WO, s, s == 2, warp, lane, a);
#pragma unroll
            for (int i = 0; i < 4; i++) mma16816(c[i], a[i], b0, b1);
        }
        float v0, v1;
        pick2(c, tig, v0, v1);
        PUBLISH_Y(cta);
    } else if (pool_head) {
        uint32_t wa[2][4][4];
#pragma unroll
        for (int s = 0; s < 2; s++) {
            mbar_wait(bars + 8 * (B_WO + 2 * s), 0);
            mbar_wait(bars + 8 * (B_WO + 2 * s + 1), 0);
            load_frags64(sb + OFF_WO, s, false, warp, lane, wa[s]);
        }
        const int c0 = 16 * warp + (lane >> 3);
        const uint32_t* po[4];
        uint32_t mo[4];
#pragma unroll
        for (int k = 0; k < 4; k++) {
            const int c = min(c0 + 4 * k, NCTA - 1), b = c / 28, j = c % 28;
            po[k] = mbox(BOX_P + 5 * (cta - C_P) + b, sel[NRED + cta - C_P] >> b) + 32 * j + 4 * (lane & 7);
            mo[k] = 896 + 4 * j - 32 * j - 4 * (lane & 7);
        }
        if (warp >= NAP) mbar_wait(bars + 8 * B_PDONE, 0);
        uint4 ov[4], ml[4];
#pragma unroll
        for (int k = 0; k < 4; k++) {
            const uint32_t w = c0 + 4 * k < NCTA ? 0 : tag;
            ov[k] = make_uint4(w, w, w, w);
            ml[k] = make_uint4(tagw(NEG_BIG, tag), w, w, w);
        }
        uint32_t bad, spin = 0;
        do {
#pragma unroll
            for (int k = 0; k < 4; k++) {
                if (bad4(ov[k], tag)) ov[k] = ldg4(po[k]);
                if (bad4(ml[k], tag)) ml[k] = ldg4(po[k] + mo[k]);
            }
            bad = 0;
#pragma unroll
            for (int k = 0; k < 4; k++) bad |= bad4(ov[k], tag) | bad4(ml[k], tag);
            spin_guard(spin);
        } while (bad);
        __syncwarp();
        float mk[4];
#pragma unroll
        for (int k = 0; k < 4; k++) mk[k] = __uint_as_float((ml[k].x & ~3u) | ((ml[k].y >> 2) & 3u));
        float M = fmaxf(fmaxf(mk[0], mk[1]), fmaxf(mk[2], mk[3]));
        M = fmaxf(M, __shfl_xor_sync(0xffffffffu, M, 8));
        M = fmaxf(M, __shfl_xor_sync(0xffffffffu, M, 16));
        float a[5] = {};
#pragma unroll
        for (int k = 0; k < 4; k++) {
            const float e = ex2(mk[k] - M);
            a[0] += e * untag(ov[k].x); a[1] += e * untag(ov[k].y); a[2] += e * untag(ov[k].z); a[3] += e * untag(ov[k].w);
            a[4] += e * untag(ml[k].z);
        }
#pragma unroll
        for (int j = 0; j < 5; j++) a[j] += __shfl_xor_sync(0xffffffffu, a[j], 8);
#pragma unroll
        for (int j = 0; j < 5; j++) a[j] += __shfl_xor_sync(0xffffffffu, a[j], 16);
        if (lane < 8) *reinterpret_cast<float4*>(red + 40 * warp + 4 * lane) = make_float4(a[0], a[1], a[2], a[3]);
        if (lane == 0) *reinterpret_cast<float2*>(red + 40 * warp + 32) = make_float2(M, a[4]);
        if (warp < NCW - 1) {
            asm volatile("bar.arrive 7, %0;" ::"n"(32 * NCW) : "memory");
        } else {
            bar_sync(7, 32 * NCW);
            float2 sw[NCW];
            float ow[NCW], MM = NEG_BIG;
#pragma unroll
            for (int w = 0; w < NCW; w++) {
                sw[w] = *reinterpret_cast<const float2*>(red + 40 * w + 32);
                ow[w] = red[40 * w + lane];
                MM = fmaxf(MM, sw[w].x);
            }
            float num[2] = {}, den[2] = {};
#pragma unroll
            for (int w = 0; w < NCW; w++) { const float e = ex2(sw[w].x - MM); num[w & 1] += e * ow[w]; den[w & 1] += e * sw[w].y; }
            reinterpret_cast<uint16_t*>(vec)[lane] = (uint16_t)pack2((num[0] + num[1]) * rcp(den[0] + den[1]), 0.f);
        }
        bar_sync(2, 32 * NCW);
        float c[4][4] = {};
#pragma unroll
        for (int s = 0; s < 2; s++) {
            const uint32_t b0 = vec[8 * s + tig], b1 = vec[8 * s + 4 + tig];
#pragma unroll
            for (int i = 0; i < 4; i++) mma16816(c[i], wa[s][i], b0, b1);
        }
        float v0, v1;
        pick2(c, tig, v0, v1);
        PUBLISH_Y(cta - (C_P - C_X));
    }

    {
        uint32_t ga[4][6][4];
        const int r = lane & 7, mhi = (lane >> 3) & 1, khi = lane >> 4;
        const uint32_t box = sb + (mhi ? OFF_UP : OFF_GATE) + 4096 * warp + (8 * khi + r) * 64;
        const uint32_t boxx = sb + (mhi ? OFF_UPX : OFF_GATEX) + 2048 * warp + (8 * khi + r) * 32;
#define LOAD_GU()                                                           \
        do {                                                                \
            _Pragma("unroll") for (int s = 0; s < 4; s++)                   \
                _Pragma("unroll") for (int i = 0; i < 4; i++) ldsm4t(box + s * 1024 + ((i ^ (r >> 1)) << 4), ga[s][i]); \
            if (extra) {                                                    \
                _Pragma("unroll") for (int s = 0; s < 4; s++)               \
                    _Pragma("unroll") for (int i = 0; i < 2; i++) ldsm4t(boxx + s * 512 + ((i ^ (r >> 2)) << 4), ga[s][4 + i]); \
            }                                                               \
        } while (0)
        mbar_wait(bars + 8 * (B_GU + min(warp, X1_GATE)), 0);
        bool have = false;
        const uint32_t* px = mbox(BOX_X + (cta & 3), sel[80]) + 2 * tid;
        uint2 xv = make_uint2(0, 0);
        uint32_t n = 0;
        while (true) {
            if (!have && __all_sync(0xffffffffu, mbar_test(bars + 8 * (B_GU + warp), 0))) {
                have = true;
                LOAD_GU();
            }
            if (n == 0) mbar_wait(bars + 8 * (B_GU + X1_GATE), 0);
            if (bad2(xv, tag)) xv = ldg2(px);
            if (!__any_sync(0xffffffffu, bad2(xv, tag))) break;
            spin_guard(n);
        }
        const float xa = untag(xv.x), xb = untag(xv.y);
        ln_stats_part(xa, xb, stat + 20, warp, lane);
        bar_sync(2, 32 * NCW);
        float mean, rsd;
        ln_stats_fin(stat + 20, mean, rsd);
        const uint32_t hp = ln_apply(xa, xb, mean, rsd, cb1, sbp);
        if (!have) {
            mbar_wait(bars + 8 * (B_GU + warp), 0);
            LOAD_GU();
        }
        float c[6][4] = {};
        uint32_t b[4][2];
#pragma unroll
        for (int s = 0; s < 4; s++) {
            b[s][0] = __shfl_sync(0xffffffffu, hp, 8 * s + tig);
            b[s][1] = __shfl_sync(0xffffffffu, hp, 8 * s + 4 + tig);
#pragma unroll
            for (int i = 0; i < 4; i++) mma16816(c[i], ga[s][i], b[s][0], b[s][1]);
        }
        if (extra) {
#pragma unroll
            for (int s = 0; s < 4; s++)
#pragma unroll
                for (int i = 4; i < 6; i++) mma16816(c[i], ga[s][i], b[s][0], b[s][1]);
        }
        float* rw = red + 720 + 96 * warp + 48 * (tig & 1) + 8 * (tig >> 1) + g;
#pragma unroll
        for (int i = 0; i < 6; i += 2) {
            const float lo = (tig & 1) ? c[i][2] : c[i][0], hi = (tig & 1) ? c[i + 1][2] : c[i + 1][0];
            rw[8 * i] = (tig & 2) ? hi : lo;
        }
    }
    asm volatile("bar.arrive 4, %0;" ::"n"(32 * (NCW + 2)) : "memory");

    uint32_t da[3][4][4];
    const int zb = cta >= ZA, zo = 8 * (zb ? cta - ZA : NY + cta) + g;
    uint32_t* const z0 = mbox(2 * r0 + zb, sel0 >> zb) + zo;
    uint32_t* const z1 = mbox(2 * r0 + 2 + zb, sel1 >> zb) + zo;
    const int rb = tid >= 2 * ZA;
    const uint32_t* zr = mbox(2 * cta + rb, sel[min(cta, NRED - 1)] >> rb) + 4 * (rb ? tid - 2 * ZA : 2 * NY + tid);
    asm volatile("" : "+l"(zr));
    const uint32_t ok = __ballot_sync(0xffffffffu, lane < 3 && mbar_test(bars + 8 * (B_DOWN + min(lane, 2)), 0));
    const int nd = !(ok & 1u) ? 0 : !(ok & 2u) ? 1 : !(ok & 4u) ? 2 : 3;
    __syncwarp();
    uint32_t dadr[4];
    {
        const int row = 8 * (lane >> 4) + (lane & 7);
        const uint32_t line = sb + OFF_DOWN + (9 * row + warp) * 128, x = ((lane >> 3) & 1) ^ ((row + warp) & 7);
#pragma unroll
        for (int i = 0; i < 4; i++) { dadr[i] = line + (((2 * i) ^ x) << 4); asm volatile("" : "+r"(dadr[i])); }
    }
#define LOAD_DOWN(s) _Pragma("unroll") for (int i = 0; i < 4; i++) ldsm4t(dadr[i] + (s) * (16 * 1152), da[s][i])
#pragma unroll
    for (int s = 0; s < 3; s++) if (s < nd) { LOAD_DOWN(s); }
    bar_sync(8, 32 * (NCW + 2));
    {
        float c[4][4] = {};
#pragma unroll
        for (int s = 0; s < 3; s++) {
            if (s == 2 && !extra) break;
            const uint32_t b0 = vec[24 + 8 * s + tig], b1 = vec[24 + 8 * s + 4 + tig];
            if (s >= nd) {
                mbar_wait(bars + 8 * (B_DOWN + s), 0);
                LOAD_DOWN(s);
            }
#pragma unroll
            for (int i = 0; i < 4; i++) mma16816(c[i], da[s][i], b0, b1);
        }
        float v0, v1;
        pick2(c, tig, v0, v1);
        stg1(z0, tagw(v0, tag));
        stg1(z1, tagw(v1, tag));
    }
    if (cta < NRED) {
        uint4 v = make_uint4(tag, tag, tag, tag);
        if (tid < 2 * NCTA) {
            uint32_t n = 0;
            do { v = ldg4(zr); spin_guard(n); } while (bad4(v, tag));
        }
        __syncwarp();
        const float k = warp_cols(untag(v.x), untag(v.y), untag(v.z), untag(v.w), lane);
        if (lane < 8) red[12 * lane + warp] = k;
        asm volatile("bar.arrive 6, %0;" ::"n"(32 * (NCW + 2)) : "memory");
    }
}

typedef CUresult (*EncodeFn)(CUtensorMap*, CUtensorMapDataType, cuuint32_t, void*, const cuuint64_t*, const cuuint64_t*,
                             const cuuint32_t*, const cuuint32_t*, CUtensorMapInterleave, CUtensorMapSwizzle,
                             CUtensorMapL2promotion, CUtensorMapFloatOOBfill);

void make_map(EncodeFn enc, CUtensorMap* m, void* p, uint64_t cols, uint64_t rows, uint32_t bc, uint32_t br, CUtensorMapSwizzle sw,
              CUtensorMapL2promotion promo = CU_TENSOR_MAP_L2_PROMOTION_NONE) {
    cuuint64_t gd[2] = {cols, rows};
    cuuint64_t gs[1] = {cols * 2};
    cuuint32_t bd[2] = {bc, br};
    cuuint32_t es[2] = {1, 1};
    enc(m, CU_TENSOR_MAP_DATA_TYPE_BFLOAT16, 2, p, gd, gs, bd, es, CU_TENSOR_MAP_INTERLEAVE_NONE, sw,
        promo, CU_TENSOR_MAP_FLOAT_OOB_FILL_NONE);
}

}

extern "C" void kernel_launch(void* const* d_in, const int* in_sizes, int n_in, void* d_out, int out_size) {
    (void)in_sizes; (void)n_in; (void)out_size;
    EncodeFn enc = nullptr;
    cudaDriverEntryPointQueryResult qr;
    cudaGetDriverEntryPoint("cuTensorMapEncodeTiled", (void**)&enc, cudaEnableDefault, &qr);
    Maps maps;
    make_map(enc, &maps.k, d_in[1], 64, (uint64_t)HKV * SK * 2, 64, 2 * TILE, CU_TENSOR_MAP_SWIZZLE_128B);
    make_map(enc, &maps.v, d_in[2], 64, (uint64_t)HKV * SK * 2, 64, 2 * TILE, CU_TENSOR_MAP_SWIZZLE_128B);
    make_map(enc, &maps.wmod, d_in[10], 6 * DM, DM, 32, 64, CU_TENSOR_MAP_SWIZZLE_64B);
    make_map(enc, &maps.wq, d_in[3], 4096, DM, 32, 64, CU_TENSOR_MAP_SWIZZLE_64B);
    make_map(enc, &maps.wo, d_in[4], 64, 4096 * 9, 64, 72, CU_TENSOR_MAP_SWIZZLE_128B);
    make_map(enc, &maps.gate, d_in[6], FF, DM, 32, 64, CU_TENSOR_MAP_SWIZZLE_64B, CU_TENSOR_MAP_L2_PROMOTION_L2_128B);
    make_map(enc, &maps.up, d_in[7], FF, DM, 32, 64, CU_TENSOR_MAP_SWIZZLE_64B, CU_TENSOR_MAP_L2_PROMOTION_L2_128B);
    make_map(enc, &maps.gatex, d_in[6], FF, DM, 16, 64, CU_TENSOR_MAP_SWIZZLE_32B, CU_TENSOR_MAP_L2_PROMOTION_L2_128B);
    make_map(enc, &maps.upx, d_in[7], FF, DM, 16, 64, CU_TENSOR_MAP_SWIZZLE_32B, CU_TENSOR_MAP_L2_PROMOTION_L2_128B);
    make_map(enc, &maps.gb, d_in[10], 6 * DM, DM, 8, 192, CU_TENSOR_MAP_SWIZZLE_NONE);
    make_map(enc, &maps.down, d_in[8], 64, FF * 9, 64, 72, CU_TENSOR_MAP_SWIZZLE_128B);
    cudaFuncSetAttribute(fused_kernel, cudaFuncAttributeMaxDynamicSharedMemorySize, SMEM_BYTES);
    typedef const __nv_bfloat16* P;
    const Ptrs ptr = {(P)d_in[3] + 400 * 4096, (P)d_in[0], (P)d_in[9], (__nv_bfloat16*)d_out};
    fused_kernel<<<NCTA, NTHREADS, SMEM_BYTES, cudaStreamPerThread>>>(ptr, maps);
}
```
